```python
import torch

def _softmax(x, axis=-1):
    return torch.softmax(x, dim=axis)
def _gelu(x):
    return torch.nn.functional.gelu(x, approximate="tanh")
def _silu(x):
    return torch.nn.functional.silu(x)
def _sigmoid(x):
    return torch.sigmoid(x)
def _layernorm(x, axis=-1, eps=1e-5):
    m = x.mean(dim=axis, keepdim=True)
    v = x.var(dim=axis, keepdim=True, unbiased=False)
    return (x - m) / torch.sqrt(v + eps)
def _scatter_add(tgt, idx, src, axis=0):
    return tgt.clone().index_add_(axis, idx, src)
def _segment_sum(src, seg, n):
    out = torch.zeros((n,) + src.shape[1:], dtype=src.dtype)
    return out.index_add_(0, seg, src)
def _pad(x, pw):
    flat = tuple(v for pair in reversed(pw) for v in pair)
    return torch.nn.functional.pad(x, flat)

kernel_name = 'parallel_sum__sliding_block_cached__dense_activation_silu__decode'

def setup_inputs():

    _w = (lambda a: (lambda t: t.to(torch.bfloat16) if t.is_floating_point() else t)(torch.as_tensor(a)))
    def _A_setup():
        B, Sq, D = 8, 1, 512
        Hq, Hkv, Sk, Dh = 32, 8, 4096, 128
        assert Hq % Hkv == 0, (Hq, Hkv)
        return {
            "x": _w((lambda *s: torch.randn(*s, dtype=torch.bfloat16) * 0.05)(B, Sq, D)),
            "k_cache": _w((lambda *s: torch.randn(*s, dtype=torch.bfloat16) * 3.2)(B, Hkv, Sk, Dh)),
            "v_cache": _w((lambda *s: torch.randn(*s, dtype=torch.bfloat16) * 0.8)(B, Hkv, Sk, Dh)),
            "wq": _w((lambda *s: torch.randn(*s, dtype=torch.bfloat16) * 3.2)(D, Hq * Dh) * (D ** -0.5)),
            "wo": _w((lambda *s: torch.randn(*s, dtype=torch.bfloat16) * 0.8)(Hq * Dh, D) * ((Hq * Dh) ** -0.5)),
        }
    _A_in = _A_setup()

    def _B_setup():
        B, S, D, F = 8, 1, 512, 1792
        return {
            "x": _w((lambda *s: torch.randn(*s, dtype=torch.bfloat16) * 0.05)(B, S, D)),
            "w1": _w((lambda *s: torch.randn(*s, dtype=torch.bfloat16) * 3.2)(D, F) * (D ** -0.5)),
            "w2": _w((lambda *s: torch.randn(*s, dtype=torch.bfloat16) * 0.4)(F, D) * (F ** -0.5)),
        }
    _B_in = _B_setup()

    return {
        "A_x": _A_in["x"],
        "A_k_cache": _A_in["k_cache"],
        "A_v_cache": _A_in["v_cache"],
        "A_wq": _A_in["wq"],
        "A_wo": _A_in["wo"],
        "B_x": _B_in["x"],
        "B_w1": _B_in["w1"],
        "B_w2": _B_in["w2"],
    }

def reference(A_x, A_k_cache, A_v_cache, A_wq, A_wo, B_x, B_w1, B_w2):
    def _A_ref(x, k_cache, v_cache, wq, wo):
        B, Sq, D = x.shape
        Hq, Dh = 32, 128
        Hkv, Sk = k_cache.shape[1], k_cache.shape[2]
        W = min(4096, max(256, Sk // 4))
        rep = Hq // Hkv
        q = (lambda x, *d: x.permute(*d))((x @ wq).reshape(B, Sq, Hq, Dh), 0, 2, 1, 3)
        k = (lambda x, n, axis: torch.repeat_interleave(x, n, dim=axis))(k_cache[:, :, Sk - W:, :], rep, axis=1)
        v = (lambda x, n, axis: torch.repeat_interleave(x, n, dim=axis))(v_cache[:, :, Sk - W:, :], rep, axis=1)
        scores = torch.einsum("bhqd,bhkd->bhqk", q, k) * (Dh ** -0.5)
        p = _softmax(scores, axis=-1)
        o = torch.einsum("bhqk,bhkd->bhqd", p, v)
        return (lambda x, *d: x.permute(*d))(o, 0, 2, 1, 3).reshape(B, Sq, Hq * Dh) @ wo

    def _B_ref(x, w1, w2):
        h = torch.einsum("bsd,df->bsf", x, w1)
        h = _silu(h)
        out = torch.einsum("bsf,fd->bsd", h, w2)
        return out

    x = A_x
    xn = _layernorm(x, axis=-1)
    return x + _A_ref(xn, A_k_cache, A_v_cache, A_wq, A_wo) + _B_ref(xn, B_w1, B_w2)
```

```cpp
#include <cuda_runtime.h>
#include <cuda_bf16.h>
#include <cuda.h>
#include <stdint.h>

namespace {

constexpr int NCTA = 128;
constexpr int NTHREADS = 288;
constexpr int SLOT = 16384;
constexpr int NSLOT = 12;
constexpr int NFILL = 22;
constexpr uint32_t POISON = 0xFFFFFFFFu;
constexpr uint32_t SPIN_LIMIT = 1u << 22;

#define PACE_T0_NS 800
#define PACE_TAU_NS 635
#define PACE_LEAD 2

constexpr int SM_RING = 0;
constexpr int SM_XN = NSLOT * SLOT;
constexpr int SM_RED = SM_XN + 8 * 1040;
constexpr int SM_P = SM_RED + 8 * 3 * 512;
constexpr int SM_WMAX = SM_P + 4 * 260 * 4;
constexpr int SM_WSUM = SM_WMAX + 128;
constexpr int SM_SCALE = SM_WSUM + 128;
constexpr int SM_BAR = SM_SCALE + 32;
constexpr int SM_TOTAL = SM_BAR + 32 * 8;
constexpr int SMEM_BYTES = SM_TOTAL + 1024;

struct TMaps { CUtensorMap wq, w1, v, wo, w2; };

__device__ uint32_t g_cnt[8 * 32];
__device__ __align__(128) uint32_t g_q[8 * 2048];
__device__ __align__(128) uint32_t g_h[112 * 64];
__device__ __align__(128) uint32_t g_o[NCTA * 256];
__device__ __align__(128) uint32_t g_st[NCTA * 8];
__device__ __align__(128) uint32_t g_part[8 * 32 * 128 * 4];

#define TRACE(i) do {} while (0)

__device__ __forceinline__ uint32_t clk32() { uint32_t c; asm volatile("mov.u32 %0, %clock;" : "=r"(c)); return c; }
__device__ __forceinline__ uint32_t gtime32() { uint32_t c; asm volatile("mov.u32 %0, %globaltimer_lo;" : "=r"(c)); return c; }
__device__ __forceinline__ uint32_t smem_u32(const void* p) { return (uint32_t)__cvta_generic_to_shared(p); }

__device__ __forceinline__ void mbar_init(uint32_t bar, uint32_t cnt) {
    asm volatile("mbarrier.init.shared::cta.b64 [%0], %1;" :: "r"(bar), "r"(cnt) : "memory");
}
__device__ __forceinline__ void mbar_fence_init() { asm volatile("fence.mbarrier_init.release.cluster;" ::: "memory"); }
__device__ __forceinline__ void mbar_expect_tx(uint32_t bar, uint32_t bytes) {
    asm volatile("mbarrier.arrive.expect_tx.shared::cta.b64 _, [%0], %1;" :: "r"(bar), "r"(bytes) : "memory");
}
__device__ __forceinline__ void mbar_arrive(uint32_t bar) {
    asm volatile("mbarrier.arrive.shared::cta.b64 _, [%0];" :: "r"(bar) : "memory");
}
__device__ __forceinline__ void mbar_wait0(uint32_t bar) {
    #pragma unroll 1
    for (uint32_t i = 0; i < SPIN_LIMIT; i++) {
        uint32_t ok;
        asm volatile("{\n.reg .pred p;\nmbarrier.try_wait.parity.shared::cta.b64 p, [%1], 0;\nselp.u32 %0, 1, 0, p;\n}"
                     : "=r"(ok) : "r"(bar) : "memory");
        if (ok) return;
    }
    __trap();
}
__device__ __forceinline__ void bulk_g2s(uint32_t dst, const void* src, uint32_t bytes, uint32_t bar) {
    asm volatile("cp.async.bulk.shared::cluster.global.mbarrier::complete_tx::bytes [%0], [%1], %2, [%3];"
                 :: "r"(dst), "l"(src), "r"(bytes), "r"(bar) : "memory");
}
__device__ __forceinline__ void tma2d(uint32_t dst, const CUtensorMap* tm, int c0, int c1, uint32_t bar) {
    asm volatile("cp.async.bulk.tensor.2d.shared::cluster.global.mbarrier::complete_tx::bytes [%0], [%1, {%3, %4}], [%2];"
                 :: "r"(dst), "l"(tm), "r"(bar), "r"(c0), "r"(c1) : "memory");
}
__device__ __forceinline__ void bar_consumers() { asm volatile("bar.sync 1, 256;" ::: "memory"); }

__device__ __forceinline__ uint4 lds128(uint32_t a) {
    uint4 v; asm volatile("ld.shared.v4.u32 {%0,%1,%2,%3}, [%4];" : "=r"(v.x), "=r"(v.y), "=r"(v.z), "=r"(v.w) : "r"(a)); return v;
}
__device__ __forceinline__ uint32_t lds32(uint32_t a) { uint32_t v; asm volatile("ld.shared.u32 %0, [%1];" : "=r"(v) : "r"(a)); return v; }
__device__ __forceinline__ float lds32f(uint32_t a) { float v; asm volatile("ld.shared.f32 %0, [%1];" : "=f"(v) : "r"(a)); return v; }
__device__ __forceinline__ void sts32(uint32_t a, uint32_t v) { asm volatile("st.shared.u32 [%0], %1;" :: "r"(a), "r"(v) : "memory"); }
__device__ __forceinline__ void sts32f(uint32_t a, float v) { asm volatile("st.shared.f32 [%0], %1;" :: "r"(a), "f"(v) : "memory"); }
__device__ __forceinline__ void sts128(uint32_t a, uint4 v) {
    asm volatile("st.shared.v4.u32 [%0], {%1,%2,%3,%4};" :: "r"(a), "r"(v.x), "r"(v.y), "r"(v.z), "r"(v.w) : "memory");
}
__device__ __forceinline__ void ldsm_x4_t(uint32_t (&r)[4], uint32_t a) {
    asm volatile("ldmatrix.sync.aligned.m8n8.x4.trans.shared.b16 {%0,%1,%2,%3}, [%4];"
                 : "=r"(r[0]), "=r"(r[1]), "=r"(r[2]), "=r"(r[3]) : "r"(a));
}
__device__ __forceinline__ void mma16816(float (&c)[4], uint32_t a0, uint32_t a1, uint32_t a2, uint32_t a3, uint32_t b0, uint32_t b1) {
    asm volatile("mma.sync.aligned.m16n8k16.row.col.f32.bf16.bf16.f32 {%0,%1,%2,%3}, {%4,%5,%6,%7}, {%8,%9}, {%0,%1,%2,%3};"
                 : "+f"(c[0]), "+f"(c[1]), "+f"(c[2]), "+f"(c[3]) : "r"(a0), "r"(a1), "r"(a2), "r"(a3), "r"(b0), "r"(b1));
}

__device__ __forceinline__ uint32_t ld_rlx(const uint32_t* p) {
    uint32_t v; asm volatile("ld.relaxed.gpu.global.u32 %0, [%1];" : "=r"(v) : "l"(p) : "memory"); return v;
}
__device__ __forceinline__ uint32_t ld_acq(const uint32_t* p) {
    uint32_t v; asm volatile("ld.acquire.gpu.global.u32 %0, [%1];" : "=r"(v) : "l"(p) : "memory"); return v;
}
__device__ __forceinline__ uint2 ld_rlx2(const uint32_t* p) {
    uint2 v; asm volatile("ld.relaxed.gpu.global.v2.u32 {%0,%1}, [%2];" : "=r"(v.x), "=r"(v.y) : "l"(p) : "memory"); return v;
}
__device__ __forceinline__ uint4 ld_rlx4(const uint32_t* p) {
    uint4 v; asm volatile("ld.relaxed.gpu.global.v4.u32 {%0,%1,%2,%3}, [%4];" : "=r"(v.x), "=r"(v.y), "=r"(v.z), "=r"(v.w) : "l"(p) : "memory"); return v;
}
__device__ __forceinline__ void st_rlx(uint32_t* p, uint32_t v) {
    asm volatile("st.relaxed.gpu.global.u32 [%0], %1;" :: "l"(p), "r"(v) : "memory");
}
__device__ __forceinline__ void st_rlx4(uint32_t* p, uint4 v) {
    asm volatile("st.relaxed.gpu.global.v4.u32 [%0], {%1,%2,%3,%4};" :: "l"(p), "r"(v.x), "r"(v.y), "r"(v.z), "r"(v.w) : "memory");
}
__device__ __forceinline__ bool has_poison(const uint4& v) {
    return v.x == POISON || v.y == POISON || v.z == POISON || v.w == POISON;
}
__device__ __forceinline__ uint32_t unpoison(uint32_t w) { return w == POISON ? 0x7FFFFFFFu : w; }

__device__ __forceinline__ float bf16r(float x) { return __bfloat162float(__float2bfloat16_rn(x)); }
__device__ __forceinline__ uint32_t pack_bf16(float lo, float hi) {
    uint32_t r; asm("cvt.rn.bf16x2.f32 %0, %1, %2;" : "=r"(r) : "f"(hi), "f"(lo)); return r;
}
__device__ __forceinline__ float bf_lo(uint32_t w) { return __uint_as_float(w << 16); }
__device__ __forceinline__ float bf_hi(uint32_t w) { return __uint_as_float(w & 0xFFFF0000u); }

__global__ void __launch_bounds__(NTHREADS, 1)
fused_decode_kernel(const __grid_constant__ TMaps tm, const __nv_bfloat16* __restrict__ x,
                    const __nv_bfloat16* __restrict__ kcache, __nv_bfloat16* __restrict__ out)
{
    extern __shared__ uint8_t smem_raw[];
    const uint32_t sb = (smem_u32(smem_raw) + 1023u) & ~1023u;
    const int tid = threadIdx.x, warp = tid >> 5, lane = tid & 31;
    const int cta = blockIdx.x;
    const int hkv = cta >> 4, bb = (cta >> 1) & 7, half = cta & 1;
    const int kg = cta >> 3, cg = cta & 7;
    const int g = lane >> 2, t = lane & 3;
    const uint32_t bar_full = sb + SM_BAR, bar_emptyK = bar_full + NFILL * 8, bar_emptyA = bar_emptyK + 7 * 8;
    const uint32_t bar_ready = bar_emptyA + 8;
    const int kvrow0 = (bb * 8 + hkv) * 4096 + 3072 + half * 512;

    if (warp == 8) {
        uint32_t t_start = 0;
        if (lane == 0) {
            t_start = gtime32();
            mbar_init(bar_full, 1);
            mbar_fence_init();
            mbar_expect_tx(bar_full, SLOT);
            bulk_g2s(sb, kcache + (size_t)kvrow0 * 128, SLOT, bar_full);
            asm volatile("prefetch.tensormap [%0];" :: "l"(&tm.wq));
            asm volatile("prefetch.tensormap [%0];" :: "l"(&tm.w1));
            asm volatile("prefetch.tensormap [%0];" :: "l"(&tm.v));
            asm volatile("prefetch.tensormap [%0];" :: "l"(&tm.wo));
            asm volatile("prefetch.tensormap [%0];" :: "l"(&tm.w2));
        }
        const int e = lane >> 3, gg = lane & 7;
        const int ocol = 64 * cg + 16 * (kg >> 2) + gg + 8 * (e >> 1);
        const int orow = 2 * (kg & 3) + (e & 1);
        const float xres = __bfloat162float(x[orow * 512 + ocol]);
        __syncthreads();
        if (lane == 0) {
            #pragma unroll 1
            for (int i = 1; i < NFILL; i++) {
                const int s = i >= NSLOT ? i - NSLOT : i;
                if (i >= NSLOT) mbar_wait0(s == 0 ? bar_emptyK : (s <= 3 ? bar_emptyA : bar_emptyK + (s - 3) * 8));
                if (i >= PACE_LEAD) {
                    const uint32_t due = PACE_T0_NS + (i - PACE_LEAD) * PACE_TAU_NS;
                    #pragma unroll 1
                    for (uint32_t n = 0; n < SPIN_LIMIT && gtime32() - t_start < due; n++) {}
                }
                const uint32_t bar = bar_full + i * 8, dst = sb + s * SLOT;
                if (i <= 2) {
                    mbar_expect_tx(bar, SLOT);
                    tma2d(dst, &tm.wq, cta * 32, (i - 1) * 256, bar);
                } else if (i == 3) {
                    if (cta < 112) {
                        mbar_expect_tx(bar, SLOT);
                        tma2d(dst, &tm.w1, cta * 16, 0, bar);
                        tma2d(dst + 8192, &tm.w1, cta * 16, 256, bar);
                    }
                } else if (i <= 10) {
                    mbar_expect_tx(bar, SLOT);
                    bulk_g2s(dst, kcache + ((size_t)kvrow0 + (i - 3) * 64) * 128, SLOT, bar);
                } else if (i <= 18) {
                    mbar_expect_tx(bar, SLOT);
                    tma2d(dst, &tm.v, 0, (kvrow0 + (i - 11) * 64) * 2, bar);
                } else if (i == 19) {
                    mbar_expect_tx(bar, 112 * 128);
                    tma2d(dst, &tm.w2, cg * 64, kg * 112, bar);
                } else {
                    mbar_expect_tx(bar, SLOT);
                    tma2d(dst, &tm.wo, cg * 64, kg * 256 + (i - 20) * 128, bar);
                }
            }
            TRACE(40);
        }
        __syncwarp();
        mbar_wait0(bar_ready);
        mbar_wait0(bar_full + 21 * 8);
        if (lane == 0) TRACE(41);
        const uint32_t* pp = g_part + ((size_t)(cg * 32 + e * 8) * 128 + kg * 8 + gg) * 4;
        uint4 v[8];
        #pragma unroll
        for (int i = 0; i < 8; i++) v[i] = ld_rlx4(pp + i * 512);
        #pragma unroll 1
        for (uint32_t n = 0; ; n++) {
            bool bad = false;
            #pragma unroll
            for (int i = 0; i < 8; i++) if (has_poison(v[i])) { v[i] = ld_rlx4(pp + i * 512); bad = true; }
            if (!bad) break;
            if (n > SPIN_LIMIT) __trap();
        }
        float s0 = 0.f, s1 = 0.f, s2 = 0.f, s3 = 0.f;
        #pragma unroll
        for (int i = 0; i < 8; i++) {
            s0 += __uint_as_float(v[i].x); s1 += __uint_as_float(v[i].y);
            s2 += __uint_as_float(v[i].z); s3 += __uint_as_float(v[i].w);
        }
        __syncwarp();
        {
            const bool hi = e & 2;
            float a = hi ? s0 : s2, b = hi ? s1 : s3;
            float ka = hi ? s2 : s0, kb = hi ? s3 : s1;
            ka += __shfl_xor_sync(0xffffffffu, a, 16);
            kb += __shfl_xor_sync(0xffffffffu, b, 16);
            const bool od = e & 1;
            float snd = od ? ka : kb, keep = od ? kb : ka;
            keep += __shfl_xor_sync(0xffffffffu, snd, 8);
            out[orow * 512 + ocol] = __float2bfloat16_rn(xres + keep);
        }
        if (lane == 0) TRACE(42);
        return;
    }

    const uint4 xa = *reinterpret_cast<const uint4*>(x + warp * 512 + lane * 8);
    const uint4 xb = *reinterpret_cast<const uint4*>(x + warp * 512 + 256 + lane * 8);
    uint32_t cnt0 = 0;
    if (tid == 0) cnt0 = ld_rlx(g_cnt + hkv * 32);
    if (lane == 0) {
        for (int j = 1 + warp; j < NFILL + 9; j += 8) mbar_init(bar_full + j * 8, 1);
        mbar_fence_init();
    }
    {
        const uint4 pz = make_uint4(POISON, POISON, POISON, POISON);
        st_rlx4(g_part + ((size_t)(cg * 32 + kg * 2 + (warp >> 2)) * 128 + (warp & 3) * 32 + lane) * 4, pz);
        if (tid < 64) st_rlx4(g_o + cta * 256 + tid * 4, pz);
        if (tid < 2) st_rlx4(g_st + cta * 8 + tid * 4, pz);
    }
    {
        float xv[16];
        const uint32_t xw[8] = {xa.x, xa.y, xa.z, xa.w, xb.x, xb.y, xb.z, xb.w};
        #pragma unroll
        for (int i = 0; i < 8; i++) { xv[2 * i] = bf_lo(xw[i]); xv[2 * i + 1] = bf_hi(xw[i]); }
        float s = 0.f;
        #pragma unroll
        for (int i = 0; i < 16; i++) s += xv[i];
        #pragma unroll
        for (int o = 16; o; o >>= 1) s += __shfl_xor_sync(0xffffffffu, s, o);
        const float mean = s * (1.f / 512.f);
        float q = 0.f;
        #pragma unroll
        for (int i = 0; i < 16; i++) { const float d = xv[i] - mean; q += d * d; }
        #pragma unroll
        for (int o = 16; o; o >>= 1) q += __shfl_xor_sync(0xffffffffu, q, o);
        const float mb = bf16r(mean);
        const float den = bf16r(__fsqrt_rn(bf16r(bf16r(q * (1.f / 512.f)) + 1e-5f)));
        uint32_t o[8];
        #pragma unroll
        for (int i = 0; i < 8; i++)
            o[i] = pack_bf16(__fdiv_rn(bf16r(xv[2 * i] - mb), den), __fdiv_rn(bf16r(xv[2 * i + 1] - mb), den));
        sts128(sb + SM_XN + warp * 1040 + lane * 16, make_uint4(o[0], o[1], o[2], o[3]));
        sts128(sb + SM_XN + warp * 1040 + 512 + lane * 16, make_uint4(o[4], o[5], o[6], o[7]));
    }
    __syncthreads();
    if (tid == 0) TRACE(0);

    {
        uint32_t xf[4][2];
        #pragma unroll
        for (int s = 0; s < 4; s++) {
            const uint32_t a = sb + SM_XN + g * 1040 + (warp * 64 + s * 16 + 2 * t) * 2;
            xf[s][0] = lds32(a); xf[s][1] = lds32(a + 16);
        }
        float acc[3][4] = {};
        const int mi = lane >> 3, rr = lane & 7;
        const int krow = (warp & 3) * 64 + (mi >> 1) * 8 + rr;
        mbar_wait0(bar_full + (1 + (warp >> 2)) * 8);
        #pragma unroll
        for (int s = 0; s < 4; s++) {
            const int r = krow + s * 16;
            #pragma unroll
            for (int mt = 0; mt < 2; mt++) {
                uint32_t a[4];
                ldsm_x4_t(a, sb + (1 + (warp >> 2)) * SLOT + r * 64 + (((2 * mt + (mi & 1)) ^ ((r >> 1) & 3)) << 4));
                mma16816(acc[mt], a[0], a[1], a[2], a[3], xf[s][0], xf[s][1]);
            }
        }
        if (cta < 112) {
            mbar_wait0(bar_full + 3 * 8);
            #pragma unroll
            for (int s = 0; s < 4; s++) {
                const int r = (warp >> 2) * 256 + krow + s * 16;
                uint32_t a[4];
                ldsm_x4_t(a, sb + 3 * SLOT + r * 32 + (((mi & 1) ^ ((r >> 2) & 1)) << 4));
                mma16816(acc[2], a[0], a[1], a[2], a[3], xf[s][0], xf[s][1]);
            }
        }
        #pragma unroll
        for (int mt = 0; mt < 3; mt++)
            sts128(sb + SM_RED + (warp * 3 + mt) * 512 + lane * 16,
                   make_uint4(__float_as_uint(acc[mt][0]), __float_as_uint(acc[mt][1]), __float_as_uint(acc[mt][2]), __float_as_uint(acc[mt][3])));
    }
    bar_consumers();
    if (tid == 0) { TRACE(1); mbar_arrive(bar_emptyA); }
    if (tid < 192) {
        const int tile = tid < 128 ? ((tid >> 3) & 1) : 2;
        const int b = tid < 128 ? (tid >> 4) : ((tid - 128) >> 3);
        const int j = tid & 7;
        const uint32_t a = sb + SM_RED + tile * 512 + (4 * ((2 * j) & 7) + (b >> 1)) * 16 + (2 * (j >> 2) + (b & 1)) * 4;
        float v0 = 0.f, v1 = 0.f;
        #pragma unroll
        for (int w = 0; w < 8; w++) { v0 += lds32f(a + w * 1536); v1 += lds32f(a + w * 1536 + 64); }
        if (tid < 128) {
            g_q[b * 2048 + cta * 16 + (tid & 15)] = pack_bf16(v0, v1);
        } else if (cta < 112) {
            v0 = bf16r(v0); v1 = bf16r(v1);
            v0 = __fdiv_rn(v0, 1.f + __expf(-v0));
            v1 = __fdiv_rn(v1, 1.f + __expf(-v1));
            g_h[cta * 64 + b * 8 + 2 * (j & 3) + (j >> 2)] = pack_bf16(v0, v1);
        }
    }
    bar_consumers();
    const uint32_t target = (cnt0 & ~15u) + 16u;
    if (tid == 0) {
        asm volatile("fence.acq_rel.gpu;" ::: "memory");
        asm volatile("red.relaxed.gpu.global.add.u32 [%0], 1;" :: "l"(g_cnt + hkv * 32) : "memory");
        TRACE(2);
        #pragma unroll 1
        for (uint32_t n = 0; (int32_t)(ld_acq(g_cnt + hkv * 32) - target) < 0; n++) if (n > SPIN_LIMIT) __trap();
        TRACE(3);
    }
    bar_consumers();

    float sc[4][4] = {};
    {
        uint4 qf[4];
        #pragma unroll
        for (int j = 0; j < 4; j++)
            qf[j] = ld_rlx4(g_q + bb * 2048 + hkv * 256 + (g & 3) * 64 + (4 * (j ^ (g >> 2)) + t) * 4);
        const int fill = warp == 0 ? 0 : warp + 3;
        mbar_wait0(bar_full + fill * 8);
        const uint32_t kb = sb + fill * SLOT + g * 256 + t * 16;
        #pragma unroll
        for (int j = 0; j < 4; j++) {
            #pragma unroll
            for (int mt = 0; mt < 4; mt++) {
                const uint32_t a = kb + mt * 4096 + ((j ^ (g & 1)) << 6);
                const uint4 lo = lds128(a), hi = lds128(a + 2048);
                mma16816(sc[mt], lo.x, hi.x, lo.y, hi.y, qf[j].x, qf[j].y);
                mma16816(sc[mt], lo.z, hi.z, lo.w, hi.w, qf[j].z, qf[j].w);
            }
        }
        __syncwarp();
        if (lane == 0 && warp < 7) mbar_arrive(bar_emptyK + warp * 8);
    }
    if (tid == 0) TRACE(4);
    if (tid == 224) TRACE(5);
    const bool valid = (t >> 1) == (g & 1);
    const int h0 = 2 * (t & 1);
    {
        float m0 = -INFINITY, m1 = -INFINITY;
        #pragma unroll
        for (int mt = 0; mt < 4; mt++) {
            #pragma unroll
            for (int i = 0; i < 4; i++) sc[mt][i] = bf16r(bf16r(sc[mt][i]) * 0.08838834764831845f);
            m0 = fmaxf(m0, fmaxf(sc[mt][0], sc[mt][2]));
            m1 = fmaxf(m1, fmaxf(sc[mt][1], sc[mt][3]));
        }
        if (!valid) { m0 = -INFINITY; m1 = -INFINITY; }
        #pragma unroll
        for (int o = 2; o <= 16; o <<= 1) {
            m0 = fmaxf(m0, __shfl_xor_sync(0xffffffffu, m0, o));
            m1 = fmaxf(m1, __shfl_xor_sync(0xffffffffu, m1, o));
        }
        if (lane < 2) { sts32f(sb + SM_WMAX + warp * 16 + h0 * 4, m0); sts32f(sb + SM_WMAX + warp * 16 + h0 * 4 + 4, m1); }
    }
    if (warp == 0) {
        const uint32_t tg = __shfl_sync(0xffffffffu, target, 0);
        if (lane < 8) {
            #pragma unroll 1
            for (uint32_t n = 0; (int32_t)(ld_acq(g_cnt + lane * 32) - tg) < 0; n++) if (n > SPIN_LIMIT) __trap();
        }
        __syncwarp();
        if (lane == 0) mbar_arrive(bar_ready);
    }
    bar_consumers();
    float mloc0 = -INFINITY, mloc1 = -INFINITY;
    {
        #pragma unroll
        for (int w = 0; w < 8; w++) {
            mloc0 = fmaxf(mloc0, lds32f(sb + SM_WMAX + w * 16 + h0 * 4));
            mloc1 = fmaxf(mloc1, lds32f(sb + SM_WMAX + w * 16 + h0 * 4 + 4));
        }
        const float L2E = 1.4426950408889634f;
        float l0 = 0.f, l1 = 0.f;
        const uint32_t pa = sb + SM_P + (h0 * 260 + warp * 32 + (g & 3) * 8 + (g >> 2)) * 4;
        #pragma unroll
        for (int mt = 0; mt < 4; mt++) {
            const float p0 = exp2f((sc[mt][0] - mloc0) * L2E), p2 = exp2f((sc[mt][2] - mloc0) * L2E);
            const float p1 = exp2f((sc[mt][1] - mloc1) * L2E), p3 = exp2f((sc[mt][3] - mloc1) * L2E);
            l0 += p0 + p2; l1 += p1 + p3;
            if (valid) { sts32(pa + mt * 8, pack_bf16(p0, p2)); sts32(pa + 1040 + mt * 8, pack_bf16(p1, p3)); }
        }
        if (!valid) { l0 = 0.f; l1 = 0.f; }
        #pragma unroll
        for (int o = 2; o <= 16; o <<= 1) {
            l0 += __shfl_xor_sync(0xffffffffu, l0, o);
            l1 += __shfl_xor_sync(0xffffffffu, l1, o);
        }
        if (lane < 2) { sts32f(sb + SM_WSUM + warp * 16 + h0 * 4, l0); sts32f(sb + SM_WSUM + warp * 16 + h0 * 4 + 4, l1); }
    }
    const int mtC = warp & 3, kh = warp >> 2;
    uint2 hf[4];
    #pragma unroll
    for (int i = 0; i < 4; i++) {
        const int ks = kh * 4 + i;
        hf[i] = ks < 7 ? ld_rlx2(g_h + (kg * 7 + ks) * 64 + g * 8 + 2 * t) : make_uint2(0u, 0u);
    }
    bar_consumers();
    if (tid == 0) TRACE(6);
    float lloc0 = 0.f, lloc1 = 0.f;
    #pragma unroll
    for (int w = 0; w < 8; w++) {
        lloc0 += lds32f(sb + SM_WSUM + w * 16 + h0 * 4);
        lloc1 += lds32f(sb + SM_WSUM + w * 16 + h0 * 4 + 4);
    }
    if (tid < 2) {
        st_rlx(g_st + cta * 8 + h0, unpoison(__float_as_uint(mloc0)));
        st_rlx(g_st + cta * 8 + h0 + 1, unpoison(__float_as_uint(mloc1)));
        st_rlx(g_st + cta * 8 + 4 + h0, unpoison(__float_as_uint(lloc0)));
        st_rlx(g_st + cta * 8 + 4 + h0 + 1, unpoison(__float_as_uint(lloc1)));
    }

    float oa[2][4] = {};
    float scale0, scale1;
    {
        const int mi = lane >> 3, rr = lane & 7;
        const int key = (rr >> 1) + 4 * (mi >> 1) + 8 * (rr & 1);
        const int rowp = 2 * key + (warp >> 2);
        const uint32_t voff = rowp * 128 + (((2 * (warp & 3) + (mi & 1)) ^ (rowp & 7)) << 4);
        #pragma unroll
        for (int vc = 0; vc < 8; vc++) {
            uint4 p0 = make_uint4(0u, 0u, 0u, 0u), p1 = p0;
            if (g < 4) {
                const uint32_t a = sb + SM_P + (g * 260 + vc * 32 + t * 8) * 4;
                p0 = lds128(a); p1 = lds128(a + 16);
            }
            if (vc == 4) {
                uint2 pm, pl;
                #pragma unroll 1
                for (uint32_t n = 0; ; n++) {
                    pm = ld_rlx2(g_st + (cta ^ 1) * 8 + h0);
                    pl = ld_rlx2(g_st + (cta ^ 1) * 8 + 4 + h0);
                    if (pm.x != POISON && pm.y != POISON && pl.x != POISON && pl.y != POISON) break;
                    if (n > SPIN_LIMIT) __trap();
                }
                const float L2E = 1.4426950408889634f;
                const float mo0 = __uint_as_float(pm.x), mo1 = __uint_as_float(pm.y);
                const float mg0 = fmaxf(mloc0, mo0), mg1 = fmaxf(mloc1, mo1);
                const float e0 = exp2f((mloc0 - mg0) * L2E), e1 = exp2f((mloc1 - mg1) * L2E);
                scale0 = __fdiv_rn(e0, lloc0 * e0 + __uint_as_float(pl.x) * exp2f((mo0 - mg0) * L2E));
                scale1 = __fdiv_rn(e1, lloc1 * e1 + __uint_as_float(pl.y) * exp2f((mo1 - mg1) * L2E));
            }
            const int fill = 11 + vc, slot = fill >= NSLOT ? fill - NSLOT : fill;
            mbar_wait0(bar_full + fill * 8);
            const uint32_t vb = sb + slot * SLOT + voff;
            uint32_t a0[4], a1[4], a2[4], a3[4];
            ldsm_x4_t(a0, vb); ldsm_x4_t(a1, vb + 4096); ldsm_x4_t(a2, vb + 8192); ldsm_x4_t(a3, vb + 12288);
            mma16816(oa[0], a0[0], a0[1], a0[2], a0[3], p0.x, p0.y);
            mma16816(oa[1], a1[0], a1[1], a1[2], a1[3], p0.z, p0.w);
            mma16816(oa[0], a2[0], a2[1], a2[2], a2[3], p1.x, p1.y);
            mma16816(oa[1], a3[0], a3[1], a3[2], a3[3], p1.z, p1.w);
        }
        if (tid == 0) TRACE(7);
        const uint32_t lo = pack_bf16((oa[0][0] + oa[1][0]) * scale0, (oa[0][1] + oa[1][1]) * scale1);
        const uint32_t hi = pack_bf16((oa[0][2] + oa[1][2]) * scale0, (oa[0][3] + oa[1][3]) * scale1);
        const bool odd = g & 1;
        const uint32_t y = __shfl_xor_sync(0xffffffffu, odd ? lo : hi, 4);
        const uint32_t first = odd ? y : lo, second = odd ? hi : y;
        if (t < 2) {
            uint32_t* po = g_o + cta * 256 + h0 * 64 + (warp >> 1) * 16 + (g >> 1) * 4 + (warp & 1) * 2 + (g & 1);
            st_rlx(po, unpoison(__byte_perm(first, second, 0x5410)));
            st_rlx(po + 64, unpoison(__byte_perm(first, second, 0x7632)));
        }
    }

    {
        float acc[2][4] = {};
        const int mi = lane >> 3, rr = lane & 7;
        const int wrow = (mi >> 1) * 8 + rr;
        const uint32_t woff = wrow * 128 + (((2 * mtC + (mi & 1)) ^ rr) << 4);
        mbar_wait0(bar_full + 19 * 8);
        if (tid == 0) TRACE(8);
        uint4 of[2][2][2];
        const uint32_t* po = g_o + (hkv * 16 + g * 2) * 256 + (kg & 1) * 128 + kh * 32 + t * 4;
        #pragma unroll
        for (int i = 0; i < 8; i++) of[i >> 2][(i >> 1) & 1][i & 1] = ld_rlx4(po + (i >> 2) * 64 + ((i >> 1) & 1) * 256 + (i & 1) * 16);
        #pragma unroll
        for (int i = 0; i < 4; i++) {
            if (kh * 4 + i < 7) {
                uint32_t a[4];
                ldsm_x4_t(a, sb + 7 * SLOT + (kh * 4 + i) * 2048 + woff);
                mma16816(acc[i & 1], a[0], a[1], a[2], a[3], hf[i].x, hf[i].y);
            }
        }
        #pragma unroll 1
        for (uint32_t n = 0; ; n++) {
            bool bad = false;
            #pragma unroll
            for (int i = 0; i < 8; i++) {
                uint4& r = of[i >> 2][(i >> 1) & 1][i & 1];
                if (has_poison(r)) { r = ld_rlx4(po + (i >> 2) * 64 + ((i >> 1) & 1) * 256 + (i & 1) * 16); bad = true; }
            }
            if (!bad) break;
            if (n > SPIN_LIMIT) __trap();
        }
        __syncwarp();
        if (tid == 0) TRACE(9);
        #pragma unroll
        for (int hl = 0; hl < 2; hl++) {
            mbar_wait0(bar_full + (20 + hl) * 8);
            const uint32_t wb = sb + (8 + hl) * SLOT + kh * 8192 + woff;
            uint32_t a0[4], a1[4], a2[4], a3[4];
            ldsm_x4_t(a0, wb); ldsm_x4_t(a1, wb + 2048); ldsm_x4_t(a2, wb + 4096); ldsm_x4_t(a3, wb + 6144);
            #pragma unroll
            for (int hf2 = 0; hf2 < 2; hf2++) {
                mma16816(acc[0], a0[0], a0[1], a0[2], a0[3], of[hl][hf2][0].x, of[hl][hf2][0].y);
                mma16816(acc[1], a1[0], a1[1], a1[2], a1[3], of[hl][hf2][0].z, of[hl][hf2][0].w);
                mma16816(acc[0], a2[0], a2[1], a2[2], a2[3], of[hl][hf2][1].x, of[hl][hf2][1].y);
                mma16816(acc[1], a3[0], a3[1], a3[2], a3[3], of[hl][hf2][1].z, of[hl][hf2][1].w);
            }
        }
        st_rlx4(g_part + ((size_t)(cg * 32 + kg * 2 + kh) * 128 + mtC * 32 + t * 8 + g) * 4,
                make_uint4(unpoison(__float_as_uint(acc[0][0] + acc[1][0])), unpoison(__float_as_uint(acc[0][1] + acc[1][1])),
                           unpoison(__float_as_uint(acc[0][2] + acc[1][2])), unpoison(__float_as_uint(acc[0][3] + acc[1][3]))));
        if (tid == 0) TRACE(10);
    }
}

typedef CUresult (*EncodeTiledFn)(CUtensorMap*, CUtensorMapDataType, cuuint32_t, void*, const cuuint64_t*, const cuuint64_t*,
                                  const cuuint32_t*, const cuuint32_t*, CUtensorMapInterleave, CUtensorMapSwizzle,
                                  CUtensorMapL2promotion, CUtensorMapFloatOOBfill);

void make_map(EncodeTiledFn enc, CUtensorMap* m, const void* base, uint64_t cols, uint64_t rows, uint32_t box_cols,
              uint32_t box_rows, CUtensorMapSwizzle sw) {
    cuuint64_t gd[2] = {cols, rows};
    cuuint64_t gs[1] = {cols * 2};
    cuuint32_t bd[2] = {box_cols, box_rows};
    cuuint32_t es[2] = {1, 1};
    enc(m, CU_TENSOR_MAP_DATA_TYPE_BFLOAT16, 2, const_cast<void*>(base), gd, gs, bd, es, CU_TENSOR_MAP_INTERLEAVE_NONE, sw,
        CU_TENSOR_MAP_L2_PROMOTION_L2_256B, CU_TENSOR_MAP_FLOAT_OOB_FILL_NONE);
}

}

extern "C" void kernel_launch(void* const* d_in, const int* in_sizes, int n_in, void* d_out, int out_size) {
    (void)in_sizes; (void)n_in; (void)out_size;
    static EncodeTiledFn enc = nullptr;
    if (!enc) {
        void* fn = nullptr;
        cudaDriverEntryPointQueryResult qr;
        cudaGetDriverEntryPoint("cuTensorMapEncodeTiled", &fn, cudaEnableDefault, &qr);
        enc = (EncodeTiledFn)fn;
        cudaFuncSetAttribute(fused_decode_kernel, cudaFuncAttributeMaxDynamicSharedMemorySize, SMEM_BYTES);
    }
    TMaps tm;
    make_map(enc, &tm.wq, d_in[3], 4096, 512, 32, 256, CU_TENSOR_MAP_SWIZZLE_64B);
    make_map(enc, &tm.w1, d_in[6], 1792, 512, 16, 256, CU_TENSOR_MAP_SWIZZLE_32B);
    make_map(enc, &tm.v, d_in[2], 64, 8ull * 8 * 4096 * 2, 64, 128, CU_TENSOR_MAP_SWIZZLE_128B);
    make_map(enc, &tm.wo, d_in[4], 512, 4096, 64, 128, CU_TENSOR_MAP_SWIZZLE_128B);
    make_map(enc, &tm.w2, d_in[7], 512, 1792, 64, 112, CU_TENSOR_MAP_SWIZZLE_128B);
    fused_decode_kernel<<<NCTA, NTHREADS, SMEM_BYTES, cudaStreamPerThread>>>(
        tm, (const __nv_bfloat16*)d_in[0], (const __nv_bfloat16*)d_in[1], (__nv_bfloat16*)d_out);
}
```

```cpp
#include <cuda_runtime.h>
#include <cuda_bf16.h>
#include <cuda.h>
#include <stdint.h>

namespace {

constexpr int NCTA = 128;
constexpr int NTHREADS = 320;
constexpr int SLOT = 16384;
constexpr int NSLOT = 12;
constexpr int NFILL = 22;
constexpr uint32_t POISON = 0xFFFFFFFFu;
constexpr uint32_t SPIN_LIMIT = 1u << 22;

#define PACE_T0_NS 300
#define PACE_TAU_NS 635
#define PACE_LEAD 1

constexpr int SM_RING = 0;
constexpr int SM_XN = NSLOT * SLOT;
constexpr int SM_RED = SM_XN + 8 * 1040;
constexpr int SM_P = SM_RED + 8 * 3 * 512;
constexpr int SM_WMAX = SM_P + 4 * 260 * 4;
constexpr int SM_WSUM = SM_WMAX + 128;
constexpr int SM_SCALE = SM_WSUM + 128;
constexpr int SM_BAR = SM_SCALE + 32;
constexpr int SM_TOTAL = SM_BAR + 32 * 8;
constexpr int SMEM_BYTES = SM_TOTAL + 1024;

struct TMaps { CUtensorMap wq, w1, v, wo, w2; };

__device__ uint32_t g_cnt[8 * 32];
__device__ __align__(128) uint32_t g_q[8 * 2048];
__device__ __align__(128) uint32_t g_h[112 * 64];
__device__ __align__(128) uint32_t g_o[NCTA * 256];
__device__ __align__(128) uint32_t g_st[NCTA * 8];
__device__ __align__(128) uint32_t g_part[8 * 32 * 128 * 4];

#define TRACE(i) do {} while (0)

__device__ __forceinline__ uint32_t clk32() { uint32_t c; asm volatile("mov.u32 %0, %clock;" : "=r"(c)); return c; }
__device__ __forceinline__ uint32_t gtime32() { uint32_t c; asm volatile("mov.u32 %0, %globaltimer_lo;" : "=r"(c)); return c; }
__device__ __forceinline__ uint32_t smem_u32(const void* p) { return (uint32_t)__cvta_generic_to_shared(p); }

__device__ __forceinline__ void mbar_init(uint32_t bar, uint32_t cnt) {
    asm volatile("mbarrier.init.shared::cta.b64 [%0], %1;" :: "r"(bar), "r"(cnt) : "memory");
}
__device__ __forceinline__ void mbar_fence_init() { asm volatile("fence.mbarrier_init.release.cluster;" ::: "memory"); }
__device__ __forceinline__ void mbar_expect_tx(uint32_t bar, uint32_t bytes) {
    asm volatile("mbarrier.arrive.expect_tx.shared::cta.b64 _, [%0], %1;" :: "r"(bar), "r"(bytes) : "memory");
}
__device__ __forceinline__ void mbar_arrive(uint32_t bar) {
    asm volatile("mbarrier.arrive.shared::cta.b64 _, [%0];" :: "r"(bar) : "memory");
}
__device__ __forceinline__ void mbar_wait0(uint32_t bar) {
    #pragma unroll 1
    for (uint32_t i = 0; i < SPIN_LIMIT; i++) {
        uint32_t ok;
        asm volatile("{\n.reg .pred p;\nmbarrier.try_wait.parity.shared::cta.b64 p, [%1], 0;\nselp.u32 %0, 1, 0, p;\n}"
                     : "=r"(ok) : "r"(bar) : "memory");
        if (ok) return;
    }
    __trap();
}
__device__ __forceinline__ void bulk_g2s(uint32_t dst, const void* src, uint32_t bytes, uint32_t bar) {
    asm volatile("cp.async.bulk.shared::cluster.global.mbarrier::complete_tx::bytes [%0], [%1], %2, [%3];"
                 :: "r"(dst), "l"(src), "r"(bytes), "r"(bar) : "memory");
}
__device__ __forceinline__ void tma2d(uint32_t dst, const CUtensorMap* tm, int c0, int c1, uint32_t bar) {
    asm volatile("cp.async.bulk.tensor.2d.shared::cluster.global.mbarrier::complete_tx::bytes [%0], [%1, {%3, %4}], [%2];"
                 :: "r"(dst), "l"(tm), "r"(bar), "r"(c0), "r"(c1) : "memory");
}
__device__ __forceinline__ void bar_consumers() { asm volatile("bar.sync 1, 256;" ::: "memory"); }

__device__ __forceinline__ uint4 lds128(uint32_t a) {
    uint4 v; asm volatile("ld.shared.v4.u32 {%0,%1,%2,%3}, [%4];" : "=r"(v.x), "=r"(v.y), "=r"(v.z), "=r"(v.w) : "r"(a)); return v;
}
__device__ __forceinline__ uint32_t lds32(uint32_t a) { uint32_t v; asm volatile("ld.shared.u32 %0, [%1];" : "=r"(v) : "r"(a)); return v; }
__device__ __forceinline__ float lds32f(uint32_t a) { float v; asm volatile("ld.shared.f32 %0, [%1];" : "=f"(v) : "r"(a)); return v; }
__device__ __forceinline__ void sts32(uint32_t a, uint32_t v) { asm volatile("st.shared.u32 [%0], %1;" :: "r"(a), "r"(v) : "memory"); }
__device__ __forceinline__ void sts32f(uint32_t a, float v) { asm volatile("st.shared.f32 [%0], %1;" :: "r"(a), "f"(v) : "memory"); }
__device__ __forceinline__ void sts128(uint32_t a, uint4 v) {
    asm volatile("st.shared.v4.u32 [%0], {%1,%2,%3,%4};" :: "r"(a), "r"(v.x), "r"(v.y), "r"(v.z), "r"(v.w) : "memory");
}
__device__ __forceinline__ void ldsm_x4_t(uint32_t (&r)[4], uint32_t a) {
    asm volatile("ldmatrix.sync.aligned.m8n8.x4.trans.shared.b16 {%0,%1,%2,%3}, [%4];"
                 : "=r"(r[0]), "=r"(r[1]), "=r"(r[2]), "=r"(r[3]) : "r"(a));
}
__device__ __forceinline__ void mma16816(float (&c)[4], uint32_t a0, uint32_t a1, uint32_t a2, uint32_t a3, uint32_t b0, uint32_t b1) {
    asm volatile("mma.sync.aligned.m16n8k16.row.col.f32.bf16.bf16.f32 {%0,%1,%2,%3}, {%4,%5,%6,%7}, {%8,%9}, {%0,%1,%2,%3};"
                 : "+f"(c[0]), "+f"(c[1]), "+f"(c[2]), "+f"(c[3]) : "r"(a0), "r"(a1), "r"(a2), "r"(a3), "r"(b0), "r"(b1));
}

__device__ __forceinline__ uint32_t ld_rlx(const uint32_t* p) {
    uint32_t v; asm volatile("ld.relaxed.gpu.global.u32 %0, [%1];" : "=r"(v) : "l"(p) : "memory"); return v;
}
__device__ __forceinline__ uint32_t ld_acq(const uint32_t* p) {
    uint32_t v; asm volatile("ld.acquire.gpu.global.u32 %0, [%1];" : "=r"(v) : "l"(p) : "memory"); return v;
}
__device__ __forceinline__ uint2 ld_rlx2(const uint32_t* p) {
    uint2 v; asm volatile("ld.relaxed.gpu.global.v2.u32 {%0,%1}, [%2];" : "=r"(v.x), "=r"(v.y) : "l"(p) : "memory"); return v;
}
__device__ __forceinline__ uint4 ld_rlx4(const uint32_t* p) {
    uint4 v; asm volatile("ld.relaxed.gpu.global.v4.u32 {%0,%1,%2,%3}, [%4];" : "=r"(v.x), "=r"(v.y), "=r"(v.z), "=r"(v.w) : "l"(p) : "memory"); return v;
}
__device__ __forceinline__ void st_rlx(uint32_t* p, uint32_t v) {
    asm volatile("st.relaxed.gpu.global.u32 [%0], %1;" :: "l"(p), "r"(v) : "memory");
}
__device__ __forceinline__ void st_rlx4(uint32_t* p, uint4 v) {
    asm volatile("st.relaxed.gpu.global.v4.u32 [%0], {%1,%2,%3,%4};" :: "l"(p), "r"(v.x), "r"(v.y), "r"(v.z), "r"(v.w) : "memory");
}
__device__ __forceinline__ bool has_poison(const uint4& v) {
    return v.x == POISON || v.y == POISON || v.z == POISON || v.w == POISON;
}
__device__ __forceinline__ uint32_t unpoison(uint32_t w) { return w == POISON ? 0x7FFFFFFFu : w; }

__device__ __forceinline__ float sqrt_approx(float x) { float r; asm("sqrt.approx.f32 %0, %1;" : "=f"(r) : "f"(x)); return r; }
__device__ __forceinline__ float ex2(float x) { float r; asm("ex2.approx.f32 %0, %1;" : "=f"(r) : "f"(x)); return r; }
__device__ __forceinline__ float bf16r(float x) { return __bfloat162float(__float2bfloat16_rn(x)); }
__device__ __forceinline__ uint32_t pack_bf16(float lo, float hi) {
    uint32_t r; asm("cvt.rn.bf16x2.f32 %0, %1, %2;" : "=r"(r) : "f"(hi), "f"(lo)); return r;
}
__device__ __forceinline__ float bf_lo(uint32_t w) { return __uint_as_float(w << 16); }
__device__ __forceinline__ float bf_hi(uint32_t w) { return __uint_as_float(w & 0xFFFF0000u); }

__global__ void __launch_bounds__(NTHREADS, 1)
fused_decode_kernel(const __grid_constant__ TMaps tm, const __nv_bfloat16* __restrict__ x,
                    const __nv_bfloat16* __restrict__ kcache, __nv_bfloat16* __restrict__ out)
{
    extern __shared__ uint8_t smem_raw[];
    const uint32_t sb = (smem_u32(smem_raw) + 1023u) & ~1023u;
    const int tid = threadIdx.x, warp = tid >> 5, lane = tid & 31;
    const int cta = blockIdx.x;
    const int hkv = cta >> 4, bb = (cta >> 1) & 7, half = cta & 1;
    const int kg = cta >> 3, cg = cta & 7;
    const int g = lane >> 2, t = lane & 3;
    const uint32_t bar_full = sb + SM_BAR, bar_emptyK = bar_full + NFILL * 8, bar_emptyA = bar_emptyK + 7 * 8;
    const uint32_t bar_grp = bar_emptyA + 8;
    const uint32_t bar_ready = bar_grp + 8;
    const int kvrow0 = (bb * 8 + hkv) * 4096 + 3072 + half * 512;

    if (warp == 8) {
        uint32_t t_start = 0;
        if (lane == 0) {
            t_start = gtime32();
            mbar_init(bar_full, 1);
            mbar_fence_init();
            mbar_expect_tx(bar_full, SLOT);
            bulk_g2s(sb, kcache + (size_t)kvrow0 * 128, SLOT, bar_full);
            TRACE(43);
            asm volatile("prefetch.tensormap [%0];" :: "l"(&tm.wq));
            asm volatile("prefetch.tensormap [%0];" :: "l"(&tm.w1));
            asm volatile("prefetch.tensormap [%0];" :: "l"(&tm.v));
            asm volatile("prefetch.tensormap [%0];" :: "l"(&tm.wo));
            asm volatile("prefetch.tensormap [%0];" :: "l"(&tm.w2));
        }
        const int e = lane >> 3, gg = lane & 7;
        const int ocol = 64 * cg + 16 * (kg >> 2) + gg + 8 * (e >> 1);
        const int orow = 2 * (kg & 3) + (e & 1);
        const float xres = __bfloat162float(x[orow * 512 + ocol]);
        __syncthreads();
        if (lane == 0) {
            uint32_t due = PACE_T0_NS + (1 - PACE_LEAD) * PACE_TAU_NS + ((((cta * 37) & 127) * PACE_TAU_NS) >> 7);
            #pragma unroll 1
            for (int i = 1; i < NFILL; i++) {
                const int s = i < NSLOT ? i : (i < 15 ? i - 11 : (i == 15 ? 0 : i - NSLOT));
                if (i >= NSLOT) mbar_wait0(i < 15 ? bar_emptyA : bar_emptyK + (i - 15) * 8);
                if (i >= PACE_LEAD) {
                    #pragma unroll 1
                    for (uint32_t n = 0; n < SPIN_LIMIT && gtime32() - t_start < due; n++) {}
                }
                due += PACE_TAU_NS;
                if (i == 1 || i == 12 || i == 15 || i == 16) TRACE(44 + (i == 1 ? 0 : i == 12 ? 1 : i == 15 ? 2 : 3));
                const uint32_t bar = bar_full + i * 8, dst = sb + s * SLOT;
                if (i <= 2) {
                    mbar_expect_tx(bar, SLOT);
                    tma2d(dst, &tm.wq, cta * 32, (i - 1) * 256, bar);
                } else if (i == 3) {
                    if (cta < 112) {
                        mbar_expect_tx(bar, SLOT);
                        tma2d(dst, &tm.w1, cta * 16, 0, bar);
                        tma2d(dst + 8192, &tm.w1, cta * 16, 256, bar);
                    }
                } else if (i <= 10) {
                    mbar_expect_tx(bar, SLOT);
                    bulk_g2s(dst, kcache + ((size_t)kvrow0 + (i - 3) * 64) * 128, SLOT, bar);
                } else if (i <= 18) {
                    mbar_expect_tx(bar, SLOT);
                    tma2d(dst, &tm.v, 0, (kvrow0 + (i - 11) * 64) * 2, bar);
                } else if (i == 19) {
                    mbar_expect_tx(bar, 112 * 128);
                    tma2d(dst, &tm.w2, cg * 64, kg * 112, bar);
                } else {
                    mbar_expect_tx(bar, SLOT);
                    tma2d(dst, &tm.wo, cg * 64, kg * 256 + (i - 20) * 128, bar);
                }
            }
            TRACE(40);
        }
        __syncwarp();
        mbar_wait0(bar_ready);
        mbar_wait0(bar_full + 21 * 8);
        if (lane == 0) TRACE(41);
        const uint32_t* pp = g_part + ((size_t)(cg * 32 + e * 8) * 128 + kg * 8 + gg) * 4;
        uint4 v[8];
        #pragma unroll
        for (int i = 0; i < 8; i++) v[i] = ld_rlx4(pp + i * 512);
        #pragma unroll 1
        for (uint32_t n = 0; ; n++) {
            bool bad = false;
            #pragma unroll
            for (int i = 0; i < 8; i++) if (has_poison(v[i])) { v[i] = ld_rlx4(pp + i * 512); bad = true; }
            if (!bad) break;
            if (n > SPIN_LIMIT) __trap();
        }
        float s0 = 0.f, s1 = 0.f, s2 = 0.f, s3 = 0.f;
        #pragma unroll
        for (int i = 0; i < 8; i++) {
            s0 += __uint_as_float(v[i].x); s1 += __uint_as_float(v[i].y);
            s2 += __uint_as_float(v[i].z); s3 += __uint_as_float(v[i].w);
        }
        __syncwarp();
        {
            const bool hi = e & 2;
            float a = hi ? s0 : s2, b = hi ? s1 : s3;
            float ka = hi ? s2 : s0, kb = hi ? s3 : s1;
            ka += __shfl_xor_sync(0xffffffffu, a, 16);
            kb += __shfl_xor_sync(0xffffffffu, b, 16);
            const bool od = e & 1;
            float snd = od ? ka : kb, keep = od ? kb : ka;
            keep += __shfl_xor_sync(0xffffffffu, snd, 8);
            out[orow * 512 + ocol] = __float2bfloat16_rn(xres + keep);
        }
        if (lane == 0) TRACE(42);
        return;
    }

    if (warp == 9) {
        const uint32_t cnt0 = ld_rlx(g_cnt + hkv * 32);
        const uint4 pz = make_uint4(POISON, POISON, POISON, POISON);
        st_rlx4(g_q + (lane >> 2) * 2048 + cta * 16 + (lane & 3) * 4, pz);
        if (lane < 16 && cta < 112) st_rlx4(g_h + cta * 64 + lane * 4, pz);
        if (lane < 2) st_rlx4(g_st + cta * 8 + lane * 4, pz);
        st_rlx4(g_o + cta * 256 + lane * 4, pz);
        st_rlx4(g_o + cta * 256 + 128 + lane * 4, pz);
        #pragma unroll
        for (int i = 0; i < 8; i++) st_rlx4(g_part + ((size_t)(cg * 32 + kg * 2) * 128 + i * 32 + lane) * 4, pz);
        __syncthreads();
        const uint32_t target = (cnt0 & ~15u) + 16u;
        if (lane == 0) {
            TRACE(11);
            asm volatile("fence.acq_rel.gpu;" ::: "memory");
            TRACE(12);
            asm volatile("red.relaxed.gpu.global.add.u32 [%0], 1;" :: "l"(g_cnt + hkv * 32) : "memory");
            #pragma unroll 1
            for (uint32_t n = 0; (int32_t)(ld_acq(g_cnt + hkv * 32) - target) < 0; n++) if (n > SPIN_LIMIT) __trap();
            mbar_arrive(bar_grp);
            TRACE(3);
        }
        __syncwarp();
        if (lane < 8) {
            #pragma unroll 1
            for (uint32_t n = 0; (int32_t)(ld_acq(g_cnt + lane * 32) - target) < 0; n++) if (n > SPIN_LIMIT) __trap();
        }
        __syncwarp();
        if (lane == 0) { mbar_arrive(bar_ready); TRACE(20); }
        return;
    }

    const uint4 xa = *reinterpret_cast<const uint4*>(x + warp * 512 + lane * 8);
    const uint4 xb = *reinterpret_cast<const uint4*>(x + warp * 512 + 256 + lane * 8);
    if (lane == 0) {
        #pragma unroll 1
        for (int j = 1 + warp; j < NFILL + 10; j += 8) mbar_init(bar_full + j * 8, 1);
        mbar_fence_init();
    }
    __syncthreads();
    if (tid == 0) TRACE(13);
    {
        float xv[16];
        const uint32_t xw[8] = {xa.x, xa.y, xa.z, xa.w, xb.x, xb.y, xb.z, xb.w};
        #pragma unroll
        for (int i = 0; i < 8; i++) { xv[2 * i] = bf_lo(xw[i]); xv[2 * i + 1] = bf_hi(xw[i]); }
        float s = 0.f;
        #pragma unroll
        for (int i = 0; i < 16; i++) s += xv[i];
        #pragma unroll
        for (int o = 16; o; o >>= 1) s += __shfl_xor_sync(0xffffffffu, s, o);
        const float mean = s * (1.f / 512.f);
        if (tid == 0) TRACE(14);
        float q = 0.f;
        #pragma unroll
        for (int i = 0; i < 16; i++) { const float d = xv[i] - mean; q += d * d; }
        #pragma unroll
        for (int o = 16; o; o >>= 1) q += __shfl_xor_sync(0xffffffffu, q, o);
        const float mb = bf16r(mean);
        const float den = bf16r(sqrt_approx(bf16r(bf16r(q * (1.f / 512.f)) + 1e-5f)));
        uint32_t o[8];
        #pragma unroll
        for (int i = 0; i < 8; i++)
            o[i] = pack_bf16(__fdividef(bf16r(xv[2 * i] - mb), den), __fdividef(bf16r(xv[2 * i + 1] - mb), den));
        sts128(sb + SM_XN + warp * 1040 + lane * 16, make_uint4(o[0], o[1], o[2], o[3]));
        sts128(sb + SM_XN + warp * 1040 + 512 + lane * 16, make_uint4(o[4], o[5], o[6], o[7]));
    }
    if (tid == 0) TRACE(15);
    bar_consumers();
    if (tid == 0) TRACE(0);

    {
        uint32_t xf[4][2];
        #pragma unroll
        for (int s = 0; s < 4; s++) {
            const uint32_t a = sb + SM_XN + g * 1040 + (warp * 64 + s * 16 + 2 * t) * 2;
            xf[s][0] = lds32(a); xf[s][1] = lds32(a + 16);
        }
        float acc[3][4] = {};
        const int mi = lane >> 3, rr = lane & 7;
        const int krow = (warp & 3) * 64 + (mi >> 1) * 8 + rr;
        mbar_wait0(bar_full + (1 + (warp >> 2)) * 8);
        if (tid == 0) TRACE(16);
        if (tid == 128) TRACE(17);
        #pragma unroll
        for (int s = 0; s < 4; s++) {
            const int r = krow + s * 16;
            #pragma unroll
            for (int mt = 0; mt < 2; mt++) {
                uint32_t a[4];
                ldsm_x4_t(a, sb + (1 + (warp >> 2)) * SLOT + r * 64 + (((2 * mt + (mi & 1)) ^ ((r >> 1) & 3)) << 4));
                mma16816(acc[mt], a[0], a[1], a[2], a[3], xf[s][0], xf[s][1]);
            }
        }
        if (cta < 112) {
            mbar_wait0(bar_full + 3 * 8);
            if (tid == 0) TRACE(18);
            #pragma unroll
            for (int s = 0; s < 4; s++) {
                const int r = (warp >> 2) * 256 + krow + s * 16;
                uint32_t a[4];
                ldsm_x4_t(a, sb + 3 * SLOT + r * 32 + (((mi & 1) ^ ((r >> 2) & 1)) << 4));
                mma16816(acc[2], a[0], a[1], a[2], a[3], xf[s][0], xf[s][1]);
            }
        }
        #pragma unroll
        for (int mt = 0; mt < 3; mt++)
            sts128(sb + SM_RED + (warp * 3 + mt) * 512 + lane * 16,
                   make_uint4(__float_as_uint(acc[mt][0]), __float_as_uint(acc[mt][1]), __float_as_uint(acc[mt][2]), __float_as_uint(acc[mt][3])));
    }
    bar_consumers();
    if (tid == 0) { TRACE(1); mbar_arrive(bar_emptyA); }
    if (tid < 192) {
        const int tile = tid < 128 ? ((tid >> 3) & 1) : 2;
        const int b = tid < 128 ? (tid >> 4) : ((tid - 128) >> 3);
        const int j = tid & 7;
        const uint32_t a = sb + SM_RED + tile * 512 + (4 * ((2 * j) & 7) + (b >> 1)) * 16 + (2 * (j >> 2) + (b & 1)) * 4;
        float v0 = 0.f, v1 = 0.f;
        #pragma unroll
        for (int w = 0; w < 8; w++) { v0 += lds32f(a + w * 1536); v1 += lds32f(a + w * 1536 + 64); }
        if (tid < 128) {
            st_rlx(g_q + b * 2048 + cta * 16 + (tid & 15), unpoison(pack_bf16(v0, v1)));
        } else if (cta < 112) {
            v0 = bf16r(v0); v1 = bf16r(v1);
            v0 = __fdividef(v0, 1.f + __expf(-v0));
            v1 = __fdividef(v1, 1.f + __expf(-v1));
            st_rlx(g_h + cta * 64 + b * 8 + 2 * (j & 3) + (j >> 2), unpoison(pack_bf16(v0, v1)));
        }
    }
    if (tid == 0) TRACE(2);

    float sc[4][4] = {};
    {
        uint4 qf[4];
        const uint32_t* pq = g_q + bb * 2048 + hkv * 256 + (g & 3) * 64 + t * 4;
        mbar_wait0(bar_grp);
        #pragma unroll 1
        for (uint32_t n = 0; ; n++) {
            bool bad = false;
            #pragma unroll
            for (int j = 0; j < 4; j++) { qf[j] = ld_rlx4(pq + 16 * (j ^ (g >> 2))); bad |= has_poison(qf[j]); }
            if (!bad) break;
            if (n > SPIN_LIMIT) __trap();
        }
        __syncwarp();
        const int fill = warp == 0 ? 0 : warp + 3;
        mbar_wait0(bar_full + fill * 8);
        if (tid == 0 && qf[3].w != 0x12345) TRACE(19);
        const uint32_t kb = sb + fill * SLOT + g * 256 + t * 16;
        #pragma unroll
        for (int j = 0; j < 4; j++) {
            #pragma unroll
            for (int mt = 0; mt < 4; mt++) {
                const uint32_t a = kb + mt * 4096 + ((j ^ (g & 1)) << 6);
                const uint4 lo = lds128(a), hi = lds128(a + 2048);
                mma16816(sc[mt], lo.x, hi.x, lo.y, hi.y, qf[j].x, qf[j].y);
                mma16816(sc[mt], lo.z, hi.z, lo.w, hi.w, qf[j].z, qf[j].w);
            }
        }
        __syncwarp();
        if (lane == 0 && warp < 7) mbar_arrive(bar_emptyK + warp * 8);
    }
    if (tid == 0) TRACE(4);
    if (tid == 224) TRACE(5);
    const bool valid = (t >> 1) == (g & 1);
    const int h0 = 2 * (t & 1);
    {
        float m0 = -INFINITY, m1 = -INFINITY;
        #pragma unroll
        for (int mt = 0; mt < 4; mt++) {
            #pragma unroll
            for (int i = 0; i < 4; i++) sc[mt][i] = bf16r(bf16r(sc[mt][i]) * 0.08838834764831845f);
            m0 = fmaxf(m0, fmaxf(sc[mt][0], sc[mt][2]));
            m1 = fmaxf(m1, fmaxf(sc[mt][1], sc[mt][3]));
        }
        if (!valid) { m0 = -INFINITY; m1 = -INFINITY; }
        #pragma unroll
        for (int o = 2; o <= 16; o <<= 1) {
            m0 = fmaxf(m0, __shfl_xor_sync(0xffffffffu, m0, o));
            m1 = fmaxf(m1, __shfl_xor_sync(0xffffffffu, m1, o));
        }
        if (lane < 2) { sts32f(sb + SM_WMAX + warp * 16 + h0 * 4, m0); sts32f(sb + SM_WMAX + warp * 16 + h0 * 4 + 4, m1); }
    }
    bar_consumers();
    if (tid == 0) TRACE(21);
    float mloc0 = -INFINITY, mloc1 = -INFINITY;
    {
        #pragma unroll
        for (int w = 0; w < 8; w++) {
            mloc0 = fmaxf(mloc0, lds32f(sb + SM_WMAX + w * 16 + h0 * 4));
            mloc1 = fmaxf(mloc1, lds32f(sb + SM_WMAX + w * 16 + h0 * 4 + 4));
        }
        const float L2E = 1.4426950408889634f;
        float l0 = 0.f, l1 = 0.f;
        const uint32_t pa = sb + SM_P + (h0 * 260 + warp * 32 + (g & 3) * 8 + (g >> 2)) * 4;
        #pragma unroll
        for (int mt = 0; mt < 4; mt++) {
            const float p0 = ex2((sc[mt][0] - mloc0) * L2E), p2 = ex2((sc[mt][2] - mloc0) * L2E);
            const float p1 = ex2((sc[mt][1] - mloc1) * L2E), p3 = ex2((sc[mt][3] - mloc1) * L2E);
            l0 += p0 + p2; l1 += p1 + p3;
            if (valid) { sts32(pa + mt * 8, pack_bf16(p0, p2)); sts32(pa + 1040 + mt * 8, pack_bf16(p1, p3)); }
        }
        if (!valid) { l0 = 0.f; l1 = 0.f; }
        #pragma unroll
        for (int o = 2; o <= 16; o <<= 1) {
            l0 += __shfl_xor_sync(0xffffffffu, l0, o);
            l1 += __shfl_xor_sync(0xffffffffu, l1, o);
        }
        if (lane < 2) { sts32f(sb + SM_WSUM + warp * 16 + h0 * 4, l0); sts32f(sb + SM_WSUM + warp * 16 + h0 * 4 + 4, l1); }
    }
    if (tid == 0) TRACE(22);
    const int mtC = warp & 3, kh = warp >> 2;
    uint2 hf[4];
    mbar_wait0(bar_ready);
    #pragma unroll 1
    for (uint32_t n = 0; ; n++) {
        bool bad = false;
        #pragma unroll
        for (int i = 0; i < 4; i++) {
            const int ks = kh * 4 + i;
            hf[i] = ks < 7 ? ld_rlx2(g_h + (kg * 7 + ks) * 64 + g * 8 + 2 * t) : make_uint2(0u, 0u);
            bad |= hf[i].x == POISON || hf[i].y == POISON;
        }
        if (!bad) break;
        if (n > SPIN_LIMIT) __trap();
    }
    bar_consumers();
    if (tid == 0) TRACE(6);
    float lloc0 = 0.f, lloc1 = 0.f;
    #pragma unroll
    for (int w = 0; w < 8; w++) {
        lloc0 += lds32f(sb + SM_WSUM + w * 16 + h0 * 4);
        lloc1 += lds32f(sb + SM_WSUM + w * 16 + h0 * 4 + 4);
    }
    if (tid < 2) {
        st_rlx(g_st + cta * 8 + h0, unpoison(__float_as_uint(mloc0)));
        st_rlx(g_st + cta * 8 + h0 + 1, unpoison(__float_as_uint(mloc1)));
        st_rlx(g_st + cta * 8 + 4 + h0, unpoison(__float_as_uint(lloc0)));
        st_rlx(g_st + cta * 8 + 4 + h0 + 1, unpoison(__float_as_uint(lloc1)));
    }

    float oa[2][4] = {};
    float scale0 = 0.f, scale1 = 0.f;
    {
        const int mi = lane >> 3, rr = lane & 7;
        const int key = (rr >> 1) + 4 * (mi >> 1) + 8 * (rr & 1);
        const int rowp = 2 * key + (warp >> 2);
        const uint32_t voff = rowp * 128 + (((2 * (warp & 3) + (mi & 1)) ^ (rowp & 7)) << 4);
        #pragma unroll 1
        for (int vc = 0; vc < 8; vc++) {
            uint4 p0 = make_uint4(0u, 0u, 0u, 0u), p1 = p0;
            if (g < 4) {
                const uint32_t a = sb + SM_P + (g * 260 + vc * 32 + t * 8) * 4;
                p0 = lds128(a); p1 = lds128(a + 16);
            }
            if (vc == 4) {
                uint2 pm, pl;
                #pragma unroll 1
                for (uint32_t n = 0; ; n++) {
                    pm = ld_rlx2(g_st + (cta ^ 1) * 8 + h0);
                    pl = ld_rlx2(g_st + (cta ^ 1) * 8 + 4 + h0);
                    if (pm.x != POISON && pm.y != POISON && pl.x != POISON && pl.y != POISON) break;
                    if (n > SPIN_LIMIT) __trap();
                }
                const float L2E = 1.4426950408889634f;
                const float mo0 = __uint_as_float(pm.x), mo1 = __uint_as_float(pm.y);
                const float mg0 = fmaxf(mloc0, mo0), mg1 = fmaxf(mloc1, mo1);
                const float e0 = ex2((mloc0 - mg0) * L2E), e1 = ex2((mloc1 - mg1) * L2E);
                scale0 = __fdividef(e0, lloc0 * e0 + __uint_as_float(pl.x) * ex2((mo0 - mg0) * L2E));
                scale1 = __fdividef(e1, lloc1 * e1 + __uint_as_float(pl.y) * ex2((mo1 - mg1) * L2E));
            }
            const int fill = 11 + vc, slot = vc == 0 ? 11 : (vc < 4 ? vc : (vc == 4 ? 0 : vc - 1));
            mbar_wait0(bar_full + fill * 8);
            if (tid == 0) TRACE(24 + vc);
            const uint32_t vb = sb + slot * SLOT + voff;
            uint32_t a0[4], a1[4], a2[4], a3[4];
            ldsm_x4_t(a0, vb); ldsm_x4_t(a1, vb + 4096); ldsm_x4_t(a2, vb + 8192); ldsm_x4_t(a3, vb + 12288);
            mma16816(oa[0], a0[0], a0[1], a0[2], a0[3], p0.x, p0.y);
            mma16816(oa[1], a1[0], a1[1], a1[2], a1[3], p0.z, p0.w);
            mma16816(oa[0], a2[0], a2[1], a2[2], a2[3], p1.x, p1.y);
            mma16816(oa[1], a3[0], a3[1], a3[2], a3[3], p1.z, p1.w);
        }
        if (tid == 0) TRACE(7);
        const uint32_t lo = pack_bf16((oa[0][0] + oa[1][0]) * scale0, (oa[0][1] + oa[1][1]) * scale1);
        const uint32_t hi = pack_bf16((oa[0][2] + oa[1][2]) * scale0, (oa[0][3] + oa[1][3]) * scale1);
        const bool odd = g & 1;
        const uint32_t y = __shfl_xor_sync(0xffffffffu, odd ? lo : hi, 4);
        const uint32_t first = odd ? y : lo, second = odd ? hi : y;
        if (t < 2) {
            uint32_t* po = g_o + cta * 256 + h0 * 64 + (warp >> 1) * 16 + (g >> 1) * 4 + (warp & 1) * 2 + (g & 1);
            st_rlx(po, unpoison(__byte_perm(first, second, 0x5410)));
            st_rlx(po + 64, unpoison(__byte_perm(first, second, 0x7632)));
        }
    }

    {
        float acc[2][4] = {};
        const int mi = lane >> 3, rr = lane & 7;
        const int wrow = (mi >> 1) * 8 + rr;
        const uint32_t woff = wrow * 128 + (((2 * mtC + (mi & 1)) ^ rr) << 4);
        mbar_wait0(bar_full + 19 * 8);
        if (tid == 0) TRACE(8);
        uint4 of[2][2][2];
        const uint32_t* po = g_o + (hkv * 16 + g * 2) * 256 + (kg & 1) * 128 + kh * 32 + t * 4;
        #pragma unroll
        for (int i = 0; i < 8; i++) of[i >> 2][(i >> 1) & 1][i & 1] = ld_rlx4(po + (i >> 2) * 64 + ((i >> 1) & 1) * 256 + (i & 1) * 16);
        #pragma unroll
        for (int i = 0; i < 4; i++) {
            if (kh * 4 + i < 7) {
                uint32_t a[4];
                ldsm_x4_t(a, sb + 7 * SLOT + (kh * 4 + i) * 2048 + woff);
                mma16816(acc[i & 1], a[0], a[1], a[2], a[3], hf[i].x, hf[i].y);
            }
        }
        #pragma unroll 1
        for (uint32_t n = 0; ; n++) {
            bool bad = false;
            #pragma unroll
            for (int i = 0; i < 8; i++) {
                uint4& r = of[i >> 2][(i >> 1) & 1][i & 1];
                if (has_poison(r)) { r = ld_rlx4(po + (i >> 2) * 64 + ((i >> 1) & 1) * 256 + (i & 1) * 16); bad = true; }
            }
            if (!bad) break;
            if (n > SPIN_LIMIT) __trap();
        }
        __syncwarp();
        if (tid == 0) TRACE(9);
        #pragma unroll
        for (int hl = 0; hl < 2; hl++) {
            mbar_wait0(bar_full + (20 + hl) * 8);
            const uint32_t wb = sb + (8 + hl) * SLOT + kh * 8192 + woff;
            uint32_t a0[4], a1[4], a2[4], a3[4];
            ldsm_x4_t(a0, wb); ldsm_x4_t(a1, wb + 2048); ldsm_x4_t(a2, wb + 4096); ldsm_x4_t(a3, wb + 6144);
            #pragma unroll
            for (int hf2 = 0; hf2 < 2; hf2++) {
                mma16816(acc[0], a0[0], a0[1], a0[2], a0[3], of[hl][hf2][0].x, of[hl][hf2][0].y);
                mma16816(acc[1], a1[0], a1[1], a1[2], a1[3], of[hl][hf2][0].z, of[hl][hf2][0].w);
                mma16816(acc[0], a2[0], a2[1], a2[2], a2[3], of[hl][hf2][1].x, of[hl][hf2][1].y);
                mma16816(acc[1], a3[0], a3[1], a3[2], a3[3], of[hl][hf2][1].z, of[hl][hf2][1].w);
            }
        }
        st_rlx4(g_part + ((size_t)(cg * 32 + kg * 2 + kh) * 128 + mtC * 32 + t * 8 + g) * 4,
                make_uint4(unpoison(__float_as_uint(acc[0][0] + acc[1][0])), unpoison(__float_as_uint(acc[0][1] + acc[1][1])),
                           unpoison(__float_as_uint(acc[0][2] + acc[1][2])), unpoison(__float_as_uint(acc[0][3] + acc[1][3]))));
        if (tid == 0) TRACE(10);
    }
}

typedef CUresult (*EncodeTiledFn)(CUtensorMap*, CUtensorMapDataType, cuuint32_t, void*, const cuuint64_t*, const cuuint64_t*,
                                  const cuuint32_t*, const cuuint32_t*, CUtensorMapInterleave, CUtensorMapSwizzle,
                                  CUtensorMapL2promotion, CUtensorMapFloatOOBfill);

void make_map(EncodeTiledFn enc, CUtensorMap* m, const void* base, uint64_t cols, uint64_t rows, uint32_t box_cols,
              uint32_t box_rows, CUtensorMapSwizzle sw) {
    cuuint64_t gd[2] = {cols, rows};
    cuuint64_t gs[1] = {cols * 2};
    cuuint32_t bd[2] = {box_cols, box_rows};
    cuuint32_t es[2] = {1, 1};
    enc(m, CU_TENSOR_MAP_DATA_TYPE_BFLOAT16, 2, const_cast<void*>(base), gd, gs, bd, es, CU_TENSOR_MAP_INTERLEAVE_NONE, sw,
        CU_TENSOR_MAP_L2_PROMOTION_L2_256B, CU_TENSOR_MAP_FLOAT_OOB_FILL_NONE);
}

}

extern "C" void kernel_launch(void* const* d_in, const int* in_sizes, int n_in, void* d_out, int out_size) {
    (void)in_sizes; (void)n_in; (void)out_size;
    static EncodeTiledFn enc = nullptr;
    if (!enc) {
        void* fn = nullptr;
        cudaDriverEntryPointQueryResult qr;
        cudaGetDriverEntryPoint("cuTensorMapEncodeTiled", &fn, cudaEnableDefault, &qr);
        enc = (EncodeTiledFn)fn;
        cudaFuncSetAttribute(fused_decode_kernel, cudaFuncAttributeMaxDynamicSharedMemorySize, SMEM_BYTES);
    }
    TMaps tm;
    make_map(enc, &tm.wq, d_in[3], 4096, 512, 32, 256, CU_TENSOR_MAP_SWIZZLE_64B);
    make_map(enc, &tm.w1, d_in[6], 1792, 512, 16, 256, CU_TENSOR_MAP_SWIZZLE_32B);
    make_map(enc, &tm.v, d_in[2], 64, 8ull * 8 * 4096 * 2, 64, 128, CU_TENSOR_MAP_SWIZZLE_128B);
    make_map(enc, &tm.wo, d_in[4], 512, 4096, 64, 128, CU_TENSOR_MAP_SWIZZLE_128B);
    make_map(enc, &tm.w2, d_in[7], 512, 1792, 64, 112, CU_TENSOR_MAP_SWIZZLE_128B);
    fused_decode_kernel<<<NCTA, NTHREADS, SMEM_BYTES, cudaStreamPerThread>>>(
        tm, (const __nv_bfloat16*)d_in[0], (const __nv_bfloat16*)d_in[1], (__nv_bfloat16*)d_out);
}
```

```cpp
#include <cuda_runtime.h>
#include <cuda_bf16.h>
#include <cuda.h>
#include <stdint.h>

namespace {

constexpr int NCTA = 128;
constexpr int NTHREADS = 320;
constexpr int SLOT = 16384;
constexpr int NSLOT = 12;
constexpr int NFILL = 22;
constexpr uint32_t POISON = 0xFFFFFFFFu;
constexpr uint32_t SPIN_LIMIT = 1u << 22;

#define PACE_T0_NS 300
#define PACE_TAU_NS 635
#define PACE_LEAD 1

constexpr int SM_RING = 0;
constexpr int SM_XN = NSLOT * SLOT;
constexpr int SM_RED = SM_XN + 8 * 1040;
constexpr int SM_P = SM_RED + 8 * 3 * 512;
constexpr int SM_WMAX = SM_P + 4 * 260 * 4;
constexpr int SM_WSUM = SM_WMAX + 128;
constexpr int SM_ST = SM_WSUM + 128;
constexpr int SM_Q = SM_ST + 32;
constexpr int SM_H = SM_Q + 4 * 272;
constexpr int SM_O = SM_RED;
constexpr int SM_BAR = SM_H + 7 * 256;
constexpr int NBAR = NFILL + 7 + 6;
constexpr int SM_TOTAL = SM_BAR + NBAR * 8;
constexpr int SMEM_BYTES = SM_TOTAL + 1024;

struct TMaps { CUtensorMap wq, w1, v, wo, w2; };

__device__ uint32_t g_cnt[8 * 32];
__device__ __align__(128) uint32_t g_q[8 * 2048];
__device__ __align__(128) uint32_t g_h[112 * 64];
__device__ __align__(128) uint32_t g_o[NCTA * 256];
__device__ __align__(128) uint32_t g_st[NCTA * 8];
__device__ __align__(128) uint32_t g_part[8 * 32 * 128 * 4];

#define TRACE(i) do {} while (0)

__device__ __forceinline__ uint32_t clk32() { uint32_t c; asm volatile("mov.u32 %0, %clock;" : "=r"(c)); return c; }
__device__ __forceinline__ uint32_t gtime32() { uint32_t c; asm volatile("mov.u32 %0, %globaltimer_lo;" : "=r"(c)); return c; }
__device__ __forceinline__ uint32_t smem_u32(const void* p) { return (uint32_t)__cvta_generic_to_shared(p); }

__device__ __forceinline__ void mbar_init(uint32_t bar, uint32_t cnt) {
    asm volatile("mbarrier.init.shared::cta.b64 [%0], %1;" :: "r"(bar), "r"(cnt) : "memory");
}
__device__ __forceinline__ void mbar_fence_init() { asm volatile("fence.mbarrier_init.release.cluster;" ::: "memory"); }
__device__ __forceinline__ void mbar_expect_tx(uint32_t bar, uint32_t bytes) {
    asm volatile("mbarrier.arrive.expect_tx.shared::cta.b64 _, [%0], %1;" :: "r"(bar), "r"(bytes) : "memory");
}
__device__ __forceinline__ void mbar_arrive(uint32_t bar) {
    asm volatile("mbarrier.arrive.shared::cta.b64 _, [%0];" :: "r"(bar) : "memory");
}
__device__ __forceinline__ void mbar_wait0(uint32_t bar) {
    #pragma unroll 1
    for (uint32_t i = 0; i < SPIN_LIMIT; i++) {
        uint32_t ok;
        asm volatile("{\n.reg .pred p;\nmbarrier.try_wait.parity.shared::cta.b64 p, [%1], 0;\nselp.u32 %0, 1, 0, p;\n}"
                     : "=r"(ok) : "r"(bar) : "memory");
        if (ok) return;
    }
    __trap();
}
__device__ __forceinline__ void bulk_g2s(uint32_t dst, const void* src, uint32_t bytes, uint32_t bar) {
    asm volatile("cp.async.bulk.shared::cluster.global.mbarrier::complete_tx::bytes [%0], [%1], %2, [%3];"
                 :: "r"(dst), "l"(src), "r"(bytes), "r"(bar) : "memory");
}
__device__ __forceinline__ void tma2d(uint32_t dst, const CUtensorMap* tm, int c0, int c1, uint32_t bar) {
    asm volatile("cp.async.bulk.tensor.2d.shared::cluster.global.mbarrier::complete_tx::bytes [%0], [%1, {%3, %4}], [%2];"
                 :: "r"(dst), "l"(tm), "r"(bar), "r"(c0), "r"(c1) : "memory");
}
__device__ __forceinline__ void bar_consumers() { asm volatile("bar.sync 1, 256;" ::: "memory"); }

__device__ __forceinline__ uint4 lds128(uint32_t a) {
    uint4 v; asm volatile("ld.shared.v4.u32 {%0,%1,%2,%3}, [%4];" : "=r"(v.x), "=r"(v.y), "=r"(v.z), "=r"(v.w) : "r"(a)); return v;
}
__device__ __forceinline__ uint32_t lds32(uint32_t a) { uint32_t v; asm volatile("ld.shared.u32 %0, [%1];" : "=r"(v) : "r"(a)); return v; }
__device__ __forceinline__ float lds32f(uint32_t a) { float v; asm volatile("ld.shared.f32 %0, [%1];" : "=f"(v) : "r"(a)); return v; }
__device__ __forceinline__ void sts32(uint32_t a, uint32_t v) { asm volatile("st.shared.u32 [%0], %1;" :: "r"(a), "r"(v) : "memory"); }
__device__ __forceinline__ void sts32f(uint32_t a, float v) { asm volatile("st.shared.f32 [%0], %1;" :: "r"(a), "f"(v) : "memory"); }
__device__ __forceinline__ void sts128(uint32_t a, uint4 v) {
    asm volatile("st.shared.v4.u32 [%0], {%1,%2,%3,%4};" :: "r"(a), "r"(v.x), "r"(v.y), "r"(v.z), "r"(v.w) : "memory");
}
__device__ __forceinline__ void ldsm_x4_t(uint32_t (&r)[4], uint32_t a) {
    asm volatile("ldmatrix.sync.aligned.m8n8.x4.trans.shared.b16 {%0,%1,%2,%3}, [%4];"
                 : "=r"(r[0]), "=r"(r[1]), "=r"(r[2]), "=r"(r[3]) : "r"(a));
}
__device__ __forceinline__ void mma16816(float (&c)[4], uint32_t a0, uint32_t a1, uint32_t a2, uint32_t a3, uint32_t b0, uint32_t b1) {
    asm volatile("mma.sync.aligned.m16n8k16.row.col.f32.bf16.bf16.f32 {%0,%1,%2,%3}, {%4,%5,%6,%7}, {%8,%9}, {%0,%1,%2,%3};"
                 : "+f"(c[0]), "+f"(c[1]), "+f"(c[2]), "+f"(c[3]) : "r"(a0), "r"(a1), "r"(a2), "r"(a3), "r"(b0), "r"(b1));
}

__device__ __forceinline__ uint32_t ld_rlx(const uint32_t* p) {
    uint32_t v; asm volatile("ld.relaxed.gpu.global.u32 %0, [%1];" : "=r"(v) : "l"(p) : "memory"); return v;
}
__device__ __forceinline__ uint32_t ld_acq(const uint32_t* p) {
    uint32_t v; asm volatile("ld.acquire.gpu.global.u32 %0, [%1];" : "=r"(v) : "l"(p) : "memory"); return v;
}
__device__ __forceinline__ uint2 ld_rlx2(const uint32_t* p) {
    uint2 v; asm volatile("ld.relaxed.gpu.global.v2.u32 {%0,%1}, [%2];" : "=r"(v.x), "=r"(v.y) : "l"(p) : "memory"); return v;
}
__device__ __forceinline__ uint4 ld_rlx4(const uint32_t* p) {
    uint4 v; asm volatile("ld.relaxed.gpu.global.v4.u32 {%0,%1,%2,%3}, [%4];" : "=r"(v.x), "=r"(v.y), "=r"(v.z), "=r"(v.w) : "l"(p) : "memory"); return v;
}
__device__ __forceinline__ void st_rlx(uint32_t* p, uint32_t v) {
    asm volatile("st.relaxed.gpu.global.u32 [%0], %1;" :: "l"(p), "r"(v) : "memory");
}
__device__ __forceinline__ void st_rlx4(uint32_t* p, uint4 v) {
    asm volatile("st.relaxed.gpu.global.v4.u32 [%0], {%1,%2,%3,%4};" :: "l"(p), "r"(v.x), "r"(v.y), "r"(v.z), "r"(v.w) : "memory");
}
__device__ __forceinline__ bool has_poison(const uint4& v) {
    return v.x == POISON || v.y == POISON || v.z == POISON || v.w == POISON;
}
__device__ __forceinline__ uint32_t unpoison(uint32_t w) { return w == POISON ? 0x7FFFFFFFu : w; }

__device__ __forceinline__ float sqrt_approx(float x) { float r; asm("sqrt.approx.f32 %0, %1;" : "=f"(r) : "f"(x)); return r; }
__device__ __forceinline__ float ex2(float x) { float r; asm("ex2.approx.f32 %0, %1;" : "=f"(r) : "f"(x)); return r; }
__device__ __forceinline__ float bf16r(float x) { return __bfloat162float(__float2bfloat16_rn(x)); }
__device__ __forceinline__ uint32_t pack_bf16(float lo, float hi) {
    uint32_t r; asm("cvt.rn.bf16x2.f32 %0, %1, %2;" : "=r"(r) : "f"(hi), "f"(lo)); return r;
}
__device__ __forceinline__ float bf_lo(uint32_t w) { return __uint_as_float(w << 16); }
__device__ __forceinline__ float bf_hi(uint32_t w) { return __uint_as_float(w & 0xFFFF0000u); }

__global__ void __launch_bounds__(NTHREADS, 1)
fused_decode_kernel(const __grid_constant__ TMaps tm, const __nv_bfloat16* __restrict__ x,
                    const __nv_bfloat16* __restrict__ kcache, __nv_bfloat16* __restrict__ out)
{
    extern __shared__ uint8_t smem_raw[];
    const uint32_t sb = (smem_u32(smem_raw) + 1023u) & ~1023u;
    const int tid = threadIdx.x, warp = tid >> 5, lane = tid & 31;
    const int cta = blockIdx.x;
    const int hkv = cta >> 4, bb = (cta >> 1) & 7, half = cta & 1;
    const int kg = cta >> 3, cg = cta & 7;
    const int g = lane >> 2, t = lane & 3;
    const uint32_t bar_full = sb + SM_BAR, bar_emptyK = bar_full + NFILL * 8, bar_emptyA = bar_emptyK + 7 * 8;
    const uint32_t bar_q = bar_emptyA + 8, bar_st = bar_q + 8, bar_o = bar_st + 8, bar_cdone = bar_o + 8, bar_ready = bar_cdone + 8;
    const int kvrow0 = (bb * 8 + hkv) * 4096 + 3072 + half * 512;

    uint32_t t_start = 0;
    if (tid == 256) {
        mbar_init(bar_full, 1);
        mbar_fence_init();
        mbar_expect_tx(bar_full, SLOT);
        bulk_g2s(sb, kcache + (size_t)kvrow0 * 128, SLOT, bar_full);
        t_start = gtime32();
        TRACE(43);
    }

    if (warp == 8) {
        if (lane == 0) {
            asm volatile("prefetch.tensormap [%0];" :: "l"(&tm.wq));
            asm volatile("prefetch.tensormap [%0];" :: "l"(&tm.w1));
            asm volatile("prefetch.tensormap [%0];" :: "l"(&tm.v));
            asm volatile("prefetch.tensormap [%0];" :: "l"(&tm.wo));
            asm volatile("prefetch.tensormap [%0];" :: "l"(&tm.w2));
        }
        __syncthreads();
        const int e = lane >> 3, gg = lane & 7;
        const int ocol = 64 * cg + 16 * (kg >> 2) + gg + 8 * (e >> 1);
        const int orow = 2 * (kg & 3) + (e & 1);
        const __nv_bfloat16 xres = x[orow * 512 + ocol];
        if (lane == 0) {
            uint32_t due = PACE_T0_NS + (1 - PACE_LEAD) * PACE_TAU_NS + ((((cta * 37) & 127) * PACE_TAU_NS) >> 7);
            #pragma unroll 1
            for (int i = 1; i < NFILL; i++) {
                const int s = i < NSLOT ? i : (i < 15 ? i - 11 : (i == 15 ? 0 : i - NSLOT));
                if (i >= NSLOT) mbar_wait0(i < 15 ? bar_emptyA : bar_emptyK + (i - 15) * 8);
                if (i >= PACE_LEAD) {
                    #pragma unroll 1
                    for (uint32_t n = 0; n < SPIN_LIMIT && gtime32() - t_start < due; n++) {}
                }
                due += PACE_TAU_NS;
                if (i == 1 || i == 12 || i == 15 || i == 16) TRACE(44 + (i == 1 ? 0 : i == 12 ? 1 : i == 15 ? 2 : 3));
                const uint32_t bar = bar_full + i * 8, dst = sb + s * SLOT;
                if (i <= 2) {
                    mbar_expect_tx(bar, SLOT);
                    tma2d(dst, &tm.wq, cta * 32, (i - 1) * 256, bar);
                } else if (i == 3) {
                    if (cta < 112) {
                        mbar_expect_tx(bar, SLOT);
                        tma2d(dst, &tm.w1, cta * 16, 0, bar);
                        tma2d(dst + 8192, &tm.w1, cta * 16, 256, bar);
                    }
                } else if (i <= 10) {
                    mbar_expect_tx(bar, SLOT);
                    bulk_g2s(dst, kcache + ((size_t)kvrow0 + (i - 3) * 64) * 128, SLOT, bar);
                } else if (i <= 18) {
                    mbar_expect_tx(bar, SLOT);
                    tma2d(dst, &tm.v, 0, (kvrow0 + (i - 11) * 64) * 2, bar);
                } else if (i == 19) {
                    mbar_expect_tx(bar, 112 * 128);
                    tma2d(dst, &tm.w2, cg * 64, kg * 112, bar);
                } else {
                    mbar_expect_tx(bar, SLOT);
                    tma2d(dst, &tm.wo, cg * 64, kg * 256 + (i - 20) * 128, bar);
                }
            }
            TRACE(40);
        }
        __syncwarp();
        mbar_wait0(bar_ready);
        mbar_wait0(bar_cdone);
        const uint32_t* pp = g_part + ((size_t)(cg * 32 + e * 8) * 128 + kg * 8 + gg) * 4;
        uint4 v[8];
        #pragma unroll
        for (int i = 0; i < 8; i++) v[i] = ld_rlx4(pp + i * 512);
        #pragma unroll 1
        for (uint32_t n = 0; ; n++) {
            bool bad = false;
            #pragma unroll
            for (int i = 0; i < 8; i++) if (has_poison(v[i])) { v[i] = ld_rlx4(pp + i * 512); bad = true; }
            if (!bad) break;
            if (n > SPIN_LIMIT) __trap();
        }
        float s0 = 0.f, s1 = 0.f, s2 = 0.f, s3 = 0.f;
        #pragma unroll
        for (int i = 0; i < 8; i++) {
            s0 += __uint_as_float(v[i].x); s1 += __uint_as_float(v[i].y);
            s2 += __uint_as_float(v[i].z); s3 += __uint_as_float(v[i].w);
        }
        __syncwarp();
        {
            const bool hi = e & 2;
            float a = hi ? s0 : s2, b = hi ? s1 : s3;
            float ka = hi ? s2 : s0, kb = hi ? s3 : s1;
            ka += __shfl_xor_sync(0xffffffffu, a, 16);
            kb += __shfl_xor_sync(0xffffffffu, b, 16);
            const bool od = e & 1;
            float snd = od ? ka : kb, keep = od ? kb : ka;
            keep += __shfl_xor_sync(0xffffffffu, snd, 8);
            out[orow * 512 + ocol] = __float2bfloat16_rn(__bfloat162float(xres) + keep);
        }
        if (lane == 0) TRACE(42);
        return;
    }

    if (warp == 9) {
        const uint32_t cnt0 = ld_rlx(g_cnt + hkv * 32);
        const uint4 pz = make_uint4(POISON, POISON, POISON, POISON);
        st_rlx4(g_q + (lane >> 2) * 2048 + cta * 16 + (lane & 3) * 4, pz);
        if (lane < 16 && cta < 112) st_rlx4(g_h + cta * 64 + lane * 4, pz);
        if (lane < 2) st_rlx4(g_st + cta * 8 + lane * 4, pz);
        st_rlx4(g_o + cta * 256 + lane * 4, pz);
        st_rlx4(g_o + cta * 256 + 128 + lane * 4, pz);
        #pragma unroll
        for (int i = 0; i < 8; i++) st_rlx4(g_part + ((size_t)(cg * 32 + kg * 2) * 128 + i * 32 + lane) * 4, pz);
        __syncthreads();
        const uint32_t target = (cnt0 & ~15u) + 16u;
        if (lane == 0) {
            TRACE(11);
            asm volatile("fence.acq_rel.gpu;" ::: "memory");
            TRACE(12);
            asm volatile("red.relaxed.gpu.global.add.u32 [%0], 1;" :: "l"(g_cnt + hkv * 32) : "memory");
            #pragma unroll 1
            for (uint32_t n = 0; (int32_t)(ld_acq(g_cnt + hkv * 32) - target) < 0; n++) if (n > SPIN_LIMIT) __trap();
            TRACE(3);
        }
        __syncwarp();
        {
            const uint32_t* pq = g_q + bb * 2048 + hkv * 256 + lane * 4;
            uint4 v0, v1;
            #pragma unroll 1
            for (uint32_t n = 0; ; n++) {
                v0 = ld_rlx4(pq); v1 = ld_rlx4(pq + 128);
                if (!has_poison(v0) && !has_poison(v1)) break;
                if (n > SPIN_LIMIT) __trap();
            }
            const uint32_t a = sb + SM_Q + (lane >> 4) * 272 + (lane & 15) * 16;
            sts128(a, v0); sts128(a + 544, v1);
            __syncwarp();
            if (lane == 0) { mbar_arrive(bar_q); TRACE(23); }
        }
        if (lane < 8) {
            #pragma unroll 1
            for (uint32_t n = 0; (int32_t)(ld_acq(g_cnt + lane * 32) - target) < 0; n++) if (n > SPIN_LIMIT) __trap();
        }
        __syncwarp();
        if (lane == 0) { mbar_arrive(bar_ready); TRACE(20); }
        mbar_wait0(bar_full + 14 * 8);
        #pragma unroll 1
        for (int i = lane; i < 114; i += 32) {
            const uint32_t* src = i < 112 ? g_h + kg * 448 + i * 4 : g_st + (cta ^ 1) * 8 + (i - 112) * 4;
            uint4 v;
            #pragma unroll 1
            for (uint32_t n = 0; ; n++) {
                v = ld_rlx4(src);
                if (!has_poison(v)) break;
                if (n > SPIN_LIMIT) __trap();
            }
            sts128(i < 112 ? sb + SM_H + i * 16 : sb + SM_ST + (i - 112) * 16, v);
        }
        __syncwarp();
        if (lane == 0) { mbar_arrive(bar_st); TRACE(32); }
        mbar_wait0(bar_full + 18 * 8);
        {
            const uint32_t* po = g_o + hkv * 16 * 256 + (kg & 1) * 128 + lane * 4;
            uint4 v[16];
            #pragma unroll
            for (int i = 0; i < 16; i++) v[i] = ld_rlx4(po + i * 256);
            #pragma unroll 1
            for (uint32_t n = 0; ; n++) {
                bool bad = false;
                #pragma unroll
                for (int i = 0; i < 16; i++) if (has_poison(v[i])) { v[i] = ld_rlx4(po + i * 256); bad = true; }
                if (!bad) break;
                if (n > SPIN_LIMIT) __trap();
            }
            #pragma unroll
            for (int i = 0; i < 16; i++) sts128(sb + SM_O + i * 544 + lane * 16, v[i]);
            __syncwarp();
            if (lane == 0) { mbar_arrive(bar_o); TRACE(33); }
        }
        return;
    }

    const uint4 xa = *reinterpret_cast<const uint4*>(x + warp * 512 + lane * 8);
    const uint4 xb = *reinterpret_cast<const uint4*>(x + warp * 512 + 256 + lane * 8);
    if (lane == 0) {
        #pragma unroll 1
        for (int j = 1 + warp; j < NBAR; j += 8) mbar_init(bar_full + j * 8, bar_full + j * 8 == bar_cdone ? 8 : 1);
        mbar_fence_init();
    }
    __syncthreads();
    if (tid == 0) TRACE(13);
    {
        float xv[16];
        const uint32_t xw[8] = {xa.x, xa.y, xa.z, xa.w, xb.x, xb.y, xb.z, xb.w};
        #pragma unroll
        for (int i = 0; i < 8; i++) { xv[2 * i] = bf_lo(xw[i]); xv[2 * i + 1] = bf_hi(xw[i]); }
        float s = 0.f;
        #pragma unroll
        for (int i = 0; i < 16; i++) s += xv[i];
        #pragma unroll
        for (int o = 16; o; o >>= 1) s += __shfl_xor_sync(0xffffffffu, s, o);
        const float mean = s * (1.f / 512.f);
        if (tid == 0) TRACE(14);
        float q = 0.f;
        #pragma unroll
        for (int i = 0; i < 16; i++) { const float d = xv[i] - mean; q += d * d; }
        #pragma unroll
        for (int o = 16; o; o >>= 1) q += __shfl_xor_sync(0xffffffffu, q, o);
        const float mb = bf16r(mean);
        const float den = bf16r(sqrt_approx(bf16r(bf16r(q * (1.f / 512.f)) + 1e-5f)));
        uint32_t o[8];
        #pragma unroll
        for (int i = 0; i < 8; i++)
            o[i] = pack_bf16(__fdividef(bf16r(xv[2 * i] - mb), den), __fdividef(bf16r(xv[2 * i + 1] - mb), den));
        sts128(sb + SM_XN + warp * 1040 + lane * 16, make_uint4(o[0], o[1], o[2], o[3]));
        sts128(sb + SM_XN + warp * 1040 + 512 + lane * 16, make_uint4(o[4], o[5], o[6], o[7]));
    }
    if (tid == 0) TRACE(15);
    bar_consumers();
    if (tid == 0) TRACE(0);

    {
        uint32_t xf[4][2];
        #pragma unroll
        for (int s = 0; s < 4; s++) {
            const uint32_t a = sb + SM_XN + g * 1040 + (warp * 64 + s * 16 + 2 * t) * 2;
            xf[s][0] = lds32(a); xf[s][1] = lds32(a + 16);
        }
        float acc[3][4] = {};
        const int mi = lane >> 3, rr = lane & 7;
        const int krow = (warp & 3) * 64 + (mi >> 1) * 8 + rr;
        mbar_wait0(bar_full + (1 + (warp >> 2)) * 8);
        if (tid == 0) TRACE(16);
        if (tid == 128) TRACE(17);
        #pragma unroll
        for (int s = 0; s < 4; s++) {
            const int r = krow + s * 16;
            #pragma unroll
            for (int mt = 0; mt < 2; mt++) {
                uint32_t a[4];
                ldsm_x4_t(a, sb + (1 + (warp >> 2)) * SLOT + r * 64 + (((2 * mt + (mi & 1)) ^ ((r >> 1) & 3)) << 4));
                mma16816(acc[mt], a[0], a[1], a[2], a[3], xf[s][0], xf[s][1]);
            }
        }
        if (cta < 112) {
            mbar_wait0(bar_full + 3 * 8);
            if (tid == 0) TRACE(18);
            #pragma unroll
            for (int s = 0; s < 4; s++) {
                const int r = (warp >> 2) * 256 + krow + s * 16;
                uint32_t a[4];
                ldsm_x4_t(a, sb + 3 * SLOT + r * 32 + (((mi & 1) ^ ((r >> 2) & 1)) << 4));
                mma16816(acc[2], a[0], a[1], a[2], a[3], xf[s][0], xf[s][1]);
            }
        }
        #pragma unroll
        for (int mt = 0; mt < 3; mt++)
            sts128(sb + SM_RED + (warp * 3 + mt) * 512 + lane * 16,
                   make_uint4(__float_as_uint(acc[mt][0]), __float_as_uint(acc[mt][1]), __float_as_uint(acc[mt][2]), __float_as_uint(acc[mt][3])));
    }
    bar_consumers();
    if (tid == 0) { TRACE(1); mbar_arrive(bar_emptyA); }
    if (tid < 192) {
        const int tile = tid < 128 ? ((tid >> 3) & 1) : 2;
        const int b = tid < 128 ? (tid >> 4) : ((tid - 128) >> 3);
        const int j = tid & 7;
        const uint32_t a = sb + SM_RED + tile * 512 + (4 * ((2 * j) & 7) + (b >> 1)) * 16 + (2 * (j >> 2) + (b & 1)) * 4;
        float v0 = 0.f, v1 = 0.f;
        #pragma unroll
        for (int w = 0; w < 8; w++) { v0 += lds32f(a + w * 1536); v1 += lds32f(a + w * 1536 + 64); }
        if (tid < 128) {
            st_rlx(g_q + b * 2048 + cta * 16 + (tid & 15), unpoison(pack_bf16(v0, v1)));
        } else if (cta < 112) {
            v0 = bf16r(v0); v1 = bf16r(v1);
            v0 = __fdividef(v0, 1.f + __expf(-v0));
            v1 = __fdividef(v1, 1.f + __expf(-v1));
            st_rlx(g_h + cta * 64 + b * 8 + 2 * (j & 3) + (j >> 2), unpoison(pack_bf16(v0, v1)));
        }
    }
    if (tid == 0) TRACE(2);

    float sc[4][4] = {};
    {
        uint4 qf[4];
        mbar_wait0(bar_q);
        #pragma unroll
        for (int j = 0; j < 4; j++) qf[j] = lds128(sb + SM_Q + (g & 3) * 272 + (4 * (j ^ (g >> 2)) + t) * 16);
        const int fill = warp == 0 ? 0 : warp + 3;
        mbar_wait0(bar_full + fill * 8);
        if (tid == 0 && qf[3].w != 0x12345) TRACE(19);
        const uint32_t kb = sb + fill * SLOT + g * 256 + t * 16;
        #pragma unroll
        for (int j = 0; j < 4; j++) {
            #pragma unroll
            for (int mt = 0; mt < 4; mt++) {
                const uint32_t a = kb + mt * 4096 + ((j ^ (g & 1)) << 6);
                const uint4 lo = lds128(a), hi = lds128(a + 2048);
                mma16816(sc[mt], lo.x, hi.x, lo.y, hi.y, qf[j].x, qf[j].y);
                mma16816(sc[mt], lo.z, hi.z, lo.w, hi.w, qf[j].z, qf[j].w);
            }
        }
        __syncwarp();
        if (lane == 0 && warp < 7) mbar_arrive(bar_emptyK + warp * 8);
    }
    if (tid == 0) TRACE(4);
    if (tid == 224) TRACE(5);
    const bool valid = (t >> 1) == (g & 1);
    const int h0 = 2 * (t & 1);
    {
        float m0 = -INFINITY, m1 = -INFINITY;
        #pragma unroll
        for (int mt = 0; mt < 4; mt++) {
            #pragma unroll
            for (int i = 0; i < 4; i++) sc[mt][i] = bf16r(bf16r(sc[mt][i]) * 0.08838834764831845f);
            m0 = fmaxf(m0, fmaxf(sc[mt][0], sc[mt][2]));
            m1 = fmaxf(m1, fmaxf(sc[mt][1], sc[mt][3]));
        }
        if (!valid) { m0 = -INFINITY; m1 = -INFINITY; }
        #pragma unroll
        for (int o = 2; o <= 16; o <<= 1) {
            m0 = fmaxf(m0, __shfl_xor_sync(0xffffffffu, m0, o));
            m1 = fmaxf(m1, __shfl_xor_sync(0xffffffffu, m1, o));
        }
        if (lane < 2) { sts32f(sb + SM_WMAX + warp * 16 + h0 * 4, m0); sts32f(sb + SM_WMAX + warp * 16 + h0 * 4 + 4, m1); }
    }
    bar_consumers();
    if (tid == 0) TRACE(21);
    float mloc0 = -INFINITY, mloc1 = -INFINITY;
    {
        #pragma unroll
        for (int w = 0; w < 8; w++) {
            mloc0 = fmaxf(mloc0, lds32f(sb + SM_WMAX + w * 16 + h0 * 4));
            mloc1 = fmaxf(mloc1, lds32f(sb + SM_WMAX + w * 16 + h0 * 4 + 4));
        }
        const float L2E = 1.4426950408889634f;
        float l0 = 0.f, l1 = 0.f;
        const uint32_t pa = sb + SM_P + (h0 * 260 + warp * 32 + (g & 3) * 8 + (g >> 2)) * 4;
        #pragma unroll
        for (int mt = 0; mt < 4; mt++) {
            const float p0 = ex2((sc[mt][0] - mloc0) * L2E), p2 = ex2((sc[mt][2] - mloc0) * L2E);
            const float p1 = ex2((sc[mt][1] - mloc1) * L2E), p3 = ex2((sc[mt][3] - mloc1) * L2E);
            l0 += p0 + p2; l1 += p1 + p3;
            if (valid) { sts32(pa + mt * 8, pack_bf16(p0, p2)); sts32(pa + 1040 + mt * 8, pack_bf16(p1, p3)); }
        }
        if (!valid) { l0 = 0.f; l1 = 0.f; }
        #pragma unroll
        for (int o = 2; o <= 16; o <<= 1) {
            l0 += __shfl_xor_sync(0xffffffffu, l0, o);
            l1 += __shfl_xor_sync(0xffffffffu, l1, o);
        }
        if (lane < 2) { sts32f(sb + SM_WSUM + warp * 16 + h0 * 4, l0); sts32f(sb + SM_WSUM + warp * 16 + h0 * 4 + 4, l1); }
    }
    if (tid == 0) TRACE(22);
    const int mtC = warp & 3, kh = warp >> 2;
    bar_consumers();
    if (tid == 0) TRACE(6);
    float lloc0 = 0.f, lloc1 = 0.f;
    #pragma unroll
    for (int w = 0; w < 8; w++) {
        lloc0 += lds32f(sb + SM_WSUM + w * 16 + h0 * 4);
        lloc1 += lds32f(sb + SM_WSUM + w * 16 + h0 * 4 + 4);
    }
    if (tid < 2) {
        st_rlx(g_st + cta * 8 + h0, unpoison(__float_as_uint(mloc0)));
        st_rlx(g_st + cta * 8 + h0 + 1, unpoison(__float_as_uint(mloc1)));
        st_rlx(g_st + cta * 8 + 4 + h0, unpoison(__float_as_uint(lloc0)));
        st_rlx(g_st + cta * 8 + 4 + h0 + 1, unpoison(__float_as_uint(lloc1)));
    }

    float oa[2][4] = {};
    float scale0 = 0.f, scale1 = 0.f;
    {
        const int mi = lane >> 3, rr = lane & 7;
        const int key = (rr >> 1) + 4 * (mi >> 1) + 8 * (rr & 1);
        const int rowp = 2 * key + (warp >> 2);
        const uint32_t voff = rowp * 128 + (((2 * (warp & 3) + (mi & 1)) ^ (rowp & 7)) << 4);
        #pragma unroll 1
        for (int vc = 0; vc < 8; vc++) {
            uint4 p0 = make_uint4(0u, 0u, 0u, 0u), p1 = p0;
            if (g < 4) {
                const uint32_t a = sb + SM_P + (g * 260 + vc * 32 + t * 8) * 4;
                p0 = lds128(a); p1 = lds128(a + 16);
            }
            if (vc == 7) {
                mbar_wait0(bar_st);
                const float L2E = 1.4426950408889634f;
                const float mo0 = lds32f(sb + SM_ST + h0 * 4), mo1 = lds32f(sb + SM_ST + h0 * 4 + 4);
                const float mg0 = fmaxf(mloc0, mo0), mg1 = fmaxf(mloc1, mo1);
                const float e0 = ex2((mloc0 - mg0) * L2E), e1 = ex2((mloc1 - mg1) * L2E);
                scale0 = __fdividef(e0, lloc0 * e0 + lds32f(sb + SM_ST + 16 + h0 * 4) * ex2((mo0 - mg0) * L2E));
                scale1 = __fdividef(e1, lloc1 * e1 + lds32f(sb + SM_ST + 20 + h0 * 4) * ex2((mo1 - mg1) * L2E));
            }
            const int fill = 11 + vc, slot = vc == 0 ? 11 : (vc < 4 ? vc : (vc == 4 ? 0 : vc - 1));
            mbar_wait0(bar_full + fill * 8);
            if (tid == 0) TRACE(24 + vc);
            const uint32_t vb = sb + slot * SLOT + voff;
            uint32_t a0[4], a1[4], a2[4], a3[4];
            ldsm_x4_t(a0, vb); ldsm_x4_t(a1, vb + 4096); ldsm_x4_t(a2, vb + 8192); ldsm_x4_t(a3, vb + 12288);
            mma16816(oa[0], a0[0], a0[1], a0[2], a0[3], p0.x, p0.y);
            mma16816(oa[1], a1[0], a1[1], a1[2], a1[3], p0.z, p0.w);
            mma16816(oa[0], a2[0], a2[1], a2[2], a2[3], p1.x, p1.y);
            mma16816(oa[1], a3[0], a3[1], a3[2], a3[3], p1.z, p1.w);
        }
        if (tid == 0) TRACE(7);
        const uint32_t lo = pack_bf16((oa[0][0] + oa[1][0]) * scale0, (oa[0][1] + oa[1][1]) * scale1);
        const uint32_t hi = pack_bf16((oa[0][2] + oa[1][2]) * scale0, (oa[0][3] + oa[1][3]) * scale1);
        const bool odd = g & 1;
        const uint32_t y = __shfl_xor_sync(0xffffffffu, odd ? lo : hi, 4);
        const uint32_t first = odd ? y : lo, second = odd ? hi : y;
        if (t < 2) {
            uint32_t* po = g_o + cta * 256 + h0 * 64 + (warp >> 1) * 16 + (g >> 1) * 4 + (warp & 1) * 2 + (g & 1);
            st_rlx(po, unpoison(__byte_perm(first, second, 0x5410)));
            st_rlx(po + 64, unpoison(__byte_perm(first, second, 0x7632)));
        }
    }

    {
        float acc[2][4] = {};
        const int mi = lane >> 3, rr = lane & 7;
        const int wrow = (mi >> 1) * 8 + rr;
        const uint32_t woff = wrow * 128 + (((2 * mtC + (mi & 1)) ^ rr) << 4);
        mbar_wait0(bar_full + 19 * 8);
        if (tid == 0) TRACE(8);
        #pragma unroll
        for (int i = 0; i < 4; i++) {
            if (kh * 4 + i < 7) {
                uint32_t a[4];
                ldsm_x4_t(a, sb + 7 * SLOT + (kh * 4 + i) * 2048 + woff);
                const uint32_t ha = sb + SM_H + (kh * 4 + i) * 256 + lane * 8;
                mma16816(acc[i & 1], a[0], a[1], a[2], a[3], lds32(ha), lds32(ha + 4));
            }
        }
        mbar_wait0(bar_o);
        if (tid == 0) TRACE(9);
        uint4 of[2][2][2];
        #pragma unroll
        for (int i = 0; i < 8; i++)
            of[i >> 2][(i >> 1) & 1][i & 1] = lds128(sb + SM_O + (2 * g + ((i >> 1) & 1)) * 544 + (i >> 2) * 256 + (kh * 2 + (i & 1)) * 64 + t * 16);
        #pragma unroll
        for (int hl = 0; hl < 2; hl++) {
            mbar_wait0(bar_full + (20 + hl) * 8);
            const uint32_t wb = sb + (8 + hl) * SLOT + kh * 8192 + woff;
            uint32_t a0[4], a1[4], a2[4], a3[4];
            ldsm_x4_t(a0, wb); ldsm_x4_t(a1, wb + 2048); ldsm_x4_t(a2, wb + 4096); ldsm_x4_t(a3, wb + 6144);
            #pragma unroll
            for (int hf2 = 0; hf2 < 2; hf2++) {
                mma16816(acc[0], a0[0], a0[1], a0[2], a0[3], of[hl][hf2][0].x, of[hl][hf2][0].y);
                mma16816(acc[1], a1[0], a1[1], a1[2], a1[3], of[hl][hf2][0].z, of[hl][hf2][0].w);
                mma16816(acc[0], a2[0], a2[1], a2[2], a2[3], of[hl][hf2][1].x, of[hl][hf2][1].y);
                mma16816(acc[1], a3[0], a3[1], a3[2], a3[3], of[hl][hf2][1].z, of[hl][hf2][1].w);
            }
        }
        st_rlx4(g_part + ((size_t)(cg * 32 + kg * 2 + kh) * 128 + mtC * 32 + t * 8 + g) * 4,
                make_uint4(unpoison(__float_as_uint(acc[0][0] + acc[1][0])), unpoison(__float_as_uint(acc[0][1] + acc[1][1])),
                           unpoison(__float_as_uint(acc[0][2] + acc[1][2])), unpoison(__float_as_uint(acc[0][3] + acc[1][3]))));
        __syncwarp();
        if (lane == 0) mbar_arrive(bar_cdone);
        if (tid == 0) TRACE(10);
    }
}

typedef CUresult (*EncodeTiledFn)(CUtensorMap*, CUtensorMapDataType, cuuint32_t, void*, const cuuint64_t*, const cuuint64_t*,
                                  const cuuint32_t*, const cuuint32_t*, CUtensorMapInterleave, CUtensorMapSwizzle,
                                  CUtensorMapL2promotion, CUtensorMapFloatOOBfill);

void make_map(EncodeTiledFn enc, CUtensorMap* m, const void* base, uint64_t cols, uint64_t rows, uint32_t box_cols,
              uint32_t box_rows, CUtensorMapSwizzle sw) {
    cuuint64_t gd[2] = {cols, rows};
    cuuint64_t gs[1] = {cols * 2};
    cuuint32_t bd[2] = {box_cols, box_rows};
    cuuint32_t es[2] = {1, 1};
    enc(m, CU_TENSOR_MAP_DATA_TYPE_BFLOAT16, 2, const_cast<void*>(base), gd, gs, bd, es, CU_TENSOR_MAP_INTERLEAVE_NONE, sw,
        CU_TENSOR_MAP_L2_PROMOTION_L2_256B, CU_TENSOR_MAP_FLOAT_OOB_FILL_NONE);
}

}

extern "C" void kernel_launch(void* const* d_in, const int* in_sizes, int n_in, void* d_out, int out_size) {
    (void)in_sizes; (void)n_in; (void)out_size;
    static EncodeTiledFn enc = nullptr;
    if (!enc) {
        void* fn = nullptr;
        cudaDriverEntryPointQueryResult qr;
        cudaGetDriverEntryPoint("cuTensorMapEncodeTiled", &fn, cudaEnableDefault, &qr);
        enc = (EncodeTiledFn)fn;
        cudaFuncSetAttribute(fused_decode_kernel, cudaFuncAttributeMaxDynamicSharedMemorySize, SMEM_BYTES);
    }
    TMaps tm;
    make_map(enc, &tm.wq, d_in[3], 4096, 512, 32, 256, CU_TENSOR_MAP_SWIZZLE_64B);
    make_map(enc, &tm.w1, d_in[6], 1792, 512, 16, 256, CU_TENSOR_MAP_SWIZZLE_32B);
    make_map(enc, &tm.v, d_in[2], 64, 8ull * 8 * 4096 * 2, 64, 128, CU_TENSOR_MAP_SWIZZLE_128B);
    make_map(enc, &tm.wo, d_in[4], 512, 4096, 64, 128, CU_TENSOR_MAP_SWIZZLE_128B);
    make_map(enc, &tm.w2, d_in[7], 512, 1792, 64, 112, CU_TENSOR_MAP_SWIZZLE_128B);
    fused_decode_kernel<<<NCTA, NTHREADS, SMEM_BYTES, cudaStreamPerThread>>>(
        tm, (const __nv_bfloat16*)d_in[0], (const __nv_bfloat16*)d_in[1], (__nv_bfloat16*)d_out);
}
```

```cpp
#include <cuda_runtime.h>
#include <cuda_bf16.h>
#include <cuda.h>
#include <stdint.h>

namespace {

constexpr int NCTA = 128;
constexpr int NTHREADS = 320;
constexpr int SLOT = 16384;
constexpr int NSLOT = 12;
constexpr int NFILL = 24;
constexpr uint32_t POISON = 0xFFFFFFFFu;
constexpr uint32_t SPIN_LIMIT = 1u << 22;

struct Pace { int t0, tau, tau_tail, first_tail; };
constexpr Pace g_pace = {100, 660, 660, 19};

constexpr int SM_RING = 0;
constexpr int SM_XN = NSLOT * SLOT;
constexpr int SM_RED = SM_XN + 8 * 1040;
constexpr int SM_P = SM_RED + 8 * 3 * 512;
constexpr int SM_WMAX = SM_P + 4 * 260 * 4;
constexpr int SM_WSUM = SM_WMAX + 128;
constexpr int SM_ST = SM_WSUM + 128;
constexpr int SM_Q = SM_ST + 32;
constexpr int SM_H = SM_Q + 4 * 272;
constexpr int SM_O = SM_RED;
constexpr int SM_BAR = SM_H + 7 * 256;
constexpr int NBAR = NFILL + 7 + 5;
constexpr int SM_TOTAL = SM_BAR + NBAR * 8;
constexpr int SMEM_BYTES = SM_TOTAL + 1024;

struct TMaps { CUtensorMap wq, w1, v, wo, w2; };

struct Scratch {
    uint32_t part[8 * 32 * 128 * 4];
    uint32_t o[NCTA * 256];
    uint32_t q[8 * 2048];
    uint32_t h[112 * 64];
    uint32_t st[NCTA * 8];
    uint32_t cnt[8 * 32];
};
__device__ __align__(128) Scratch g_scratch;

#define TRACE(i) do {} while (0)

__device__ __forceinline__ uint32_t clk32() { uint32_t c; asm volatile("mov.u32 %0, %clock;" : "=r"(c)); return c; }
__device__ __forceinline__ uint32_t gtime32() { uint32_t c; asm volatile("mov.u32 %0, %globaltimer_lo;" : "=r"(c)); return c; }
__device__ __forceinline__ uint32_t smem_u32(const void* p) { return (uint32_t)__cvta_generic_to_shared(p); }

__device__ __forceinline__ void mbar_init(uint32_t bar, uint32_t cnt) {
    asm volatile("mbarrier.init.shared::cta.b64 [%0], %1;" :: "r"(bar), "r"(cnt) : "memory");
}
__device__ __forceinline__ void mbar_fence_init() { asm volatile("fence.mbarrier_init.release.cluster;" ::: "memory"); }
__device__ __forceinline__ void mbar_expect_tx(uint32_t bar, uint32_t bytes) {
    asm volatile("mbarrier.arrive.expect_tx.shared::cta.b64 _, [%0], %1;" :: "r"(bar), "r"(bytes) : "memory");
}
__device__ __forceinline__ void mbar_arrive(uint32_t bar) {
    asm volatile("mbarrier.arrive.shared::cta.b64 _, [%0];" :: "r"(bar) : "memory");
}
__device__ __forceinline__ void mbar_wait0(uint32_t bar) {
    #pragma unroll 1
    for (uint32_t i = 0; i < SPIN_LIMIT; i++) {
        uint32_t ok;
        asm volatile("{\n.reg .pred p;\nmbarrier.try_wait.parity.shared::cta.b64 p, [%1], 0;\nselp.u32 %0, 1, 0, p;\n}"
                     : "=r"(ok) : "r"(bar) : "memory");
        if (ok) return;
    }
    __trap();
}
constexpr uint64_t EVICT_FIRST = 0x12F0000000000000ull;
__device__ __forceinline__ void bulk_g2s(uint32_t dst, const void* src, uint32_t bytes, uint32_t bar) {
    asm volatile("cp.async.bulk.shared::cluster.global.mbarrier::complete_tx::bytes.L2::cache_hint [%0], [%1], %2, [%3], %4;"
                 :: "r"(dst), "l"(src), "r"(bytes), "r"(bar), "l"(EVICT_FIRST) : "memory");
}
__device__ __forceinline__ void tma2d(uint32_t dst, const CUtensorMap* tm, int c0, int c1, uint32_t bar) {
    asm volatile("cp.async.bulk.tensor.2d.shared::cluster.global.mbarrier::complete_tx::bytes.L2::cache_hint [%0], [%1, {%3, %4}], [%2], %5;"
                 :: "r"(dst), "l"(tm), "r"(bar), "r"(c0), "r"(c1), "l"(EVICT_FIRST) : "memory");
}
__device__ __forceinline__ void bar_consumers() { asm volatile("bar.sync 1, 256;" ::: "memory"); }
__device__ __forceinline__ void bar_init_done() { asm volatile("bar.sync 2, 288;" ::: "memory"); }
__device__ __forceinline__ void bar_ln_done() { asm volatile("bar.sync 3, 288;" ::: "memory"); }

__device__ __forceinline__ uint4 lds128(uint32_t a) {
    uint4 v; asm volatile("ld.shared.v4.u32 {%0,%1,%2,%3}, [%4];" : "=r"(v.x), "=r"(v.y), "=r"(v.z), "=r"(v.w) : "r"(a)); return v;
}
__device__ __forceinline__ uint32_t lds32(uint32_t a) { uint32_t v; asm volatile("ld.shared.u32 %0, [%1];" : "=r"(v) : "r"(a)); return v; }
__device__ __forceinline__ float lds32f(uint32_t a) { float v; asm volatile("ld.shared.f32 %0, [%1];" : "=f"(v) : "r"(a)); return v; }
__device__ __forceinline__ void sts32(uint32_t a, uint32_t v) { asm volatile("st.shared.u32 [%0], %1;" :: "r"(a), "r"(v) : "memory"); }
__device__ __forceinline__ void sts32f(uint32_t a, float v) { asm volatile("st.shared.f32 [%0], %1;" :: "r"(a), "f"(v) : "memory"); }
__device__ __forceinline__ void sts128(uint32_t a, uint4 v) {
    asm volatile("st.shared.v4.u32 [%0], {%1,%2,%3,%4};" :: "r"(a), "r"(v.x), "r"(v.y), "r"(v.z), "r"(v.w) : "memory");
}
__device__ __forceinline__ void ldsm_x4_t(uint32_t (&r)[4], uint32_t a) {
    asm volatile("ldmatrix.sync.aligned.m8n8.x4.trans.shared.b16 {%0,%1,%2,%3}, [%4];"
                 : "=r"(r[0]), "=r"(r[1]), "=r"(r[2]), "=r"(r[3]) : "r"(a));
}
__device__ __forceinline__ void mma16816(float (&c)[4], uint32_t a0, uint32_t a1, uint32_t a2, uint32_t a3, uint32_t b0, uint32_t b1) {
    asm volatile("mma.sync.aligned.m16n8k16.row.col.f32.bf16.bf16.f32 {%0,%1,%2,%3}, {%4,%5,%6,%7}, {%8,%9}, {%0,%1,%2,%3};"
                 : "+f"(c[0]), "+f"(c[1]), "+f"(c[2]), "+f"(c[3]) : "r"(a0), "r"(a1), "r"(a2), "r"(a3), "r"(b0), "r"(b1));
}

__device__ __forceinline__ uint32_t ld_rlx(const uint32_t* p) {
    uint32_t v; asm volatile("ld.relaxed.gpu.global.u32 %0, [%1];" : "=r"(v) : "l"(p) : "memory"); return v;
}
__device__ __forceinline__ uint32_t ld_acq(const uint32_t* p) {
    uint32_t v; asm volatile("ld.acquire.gpu.global.u32 %0, [%1];" : "=r"(v) : "l"(p) : "memory"); return v;
}
__device__ __forceinline__ uint2 ld_rlx2(const uint32_t* p) {
    uint2 v; asm volatile("ld.relaxed.gpu.global.v2.u32 {%0,%1}, [%2];" : "=r"(v.x), "=r"(v.y) : "l"(p) : "memory"); return v;
}
__device__ __forceinline__ uint4 ld_rlx4(const uint32_t* p) {
    uint4 v; asm volatile("ld.relaxed.gpu.global.v4.u32 {%0,%1,%2,%3}, [%4];" : "=r"(v.x), "=r"(v.y), "=r"(v.z), "=r"(v.w) : "l"(p) : "memory"); return v;
}
__device__ __forceinline__ void st_rlx(uint32_t* p, uint32_t v) {
    asm volatile("st.relaxed.gpu.global.u32 [%0], %1;" :: "l"(p), "r"(v) : "memory");
}
__device__ __forceinline__ void st_rlx4(uint32_t* p, uint4 v) {
    asm volatile("st.relaxed.gpu.global.v4.u32 [%0], {%1,%2,%3,%4};" :: "l"(p), "r"(v.x), "r"(v.y), "r"(v.z), "r"(v.w) : "memory");
}
__device__ __forceinline__ bool has_poison(const uint4& v) {
    return v.x == POISON || v.y == POISON || v.z == POISON || v.w == POISON;
}
__device__ __forceinline__ uint32_t unpoison(uint32_t w) { return w == POISON ? 0x7FFFFFFFu : w; }

__device__ __forceinline__ float sqrt_approx(float x) { float r; asm("sqrt.approx.f32 %0, %1;" : "=f"(r) : "f"(x)); return r; }
__device__ __forceinline__ float ex2(float x) { float r; asm("ex2.approx.f32 %0, %1;" : "=f"(r) : "f"(x)); return r; }
__device__ __forceinline__ float bf16r(float x) { return __bfloat162float(__float2bfloat16_rn(x)); }
__device__ __forceinline__ uint32_t pack_bf16(float lo, float hi) {
    uint32_t r; asm("cvt.rn.bf16x2.f32 %0, %1, %2;" : "=r"(r) : "f"(hi), "f"(lo)); return r;
}
__device__ __forceinline__ float bf_lo(uint32_t w) { return __uint_as_float(w << 16); }
__device__ __forceinline__ float bf_hi(uint32_t w) { return __uint_as_float(w & 0xFFFF0000u); }

__global__ void __launch_bounds__(NTHREADS, 1)
fused_decode_kernel(const __nv_bfloat16* __restrict__ kcache, const __nv_bfloat16* __restrict__ x,
                    __nv_bfloat16* __restrict__ out, Scratch* __restrict__ scr, const Pace pace,
                    const __grid_constant__ TMaps tm)
{
    extern __shared__ uint8_t smem_raw[];
    const uint32_t sb = (smem_u32(smem_raw) + 1023u) & ~1023u;
    const int tid = threadIdx.x, warp = tid >> 5, lane = tid & 31;
    const int cta = blockIdx.x;
    const int hkv = cta >> 4, bb = (cta >> 1) & 7, half = cta & 1;
    const int kg = cta >> 3, cg = cta & 7;
    const int g = lane >> 2, t = lane & 3;
    const uint32_t bar_full = sb + SM_BAR, bar_emptyK = bar_full + NFILL * 8, bar_emptyA = bar_emptyK + 7 * 8;
    const uint32_t bar_q = bar_emptyA + 8, bar_st = bar_q + 8, bar_cdone = bar_st + 8, bar_ready = bar_cdone + 8;
    const int kvrow0 = (bb * 8 + hkv) * 4096 + 3072 + half * 512;

    uint32_t t_start = 0;
    if (tid == 256) {
        mbar_init(bar_full, 1);
        mbar_fence_init();
        mbar_expect_tx(bar_full, SLOT);
        bulk_g2s(sb, kcache + (size_t)kvrow0 * 128, SLOT, bar_full);
        t_start = gtime32();
        TRACE(43);
    }

    if (warp == 8) {
        if (lane == 0) {
            asm volatile("prefetch.tensormap [%0];" :: "l"(&tm.wq));
            asm volatile("prefetch.tensormap [%0];" :: "l"(&tm.w1));
            asm volatile("prefetch.tensormap [%0];" :: "l"(&tm.v));
            asm volatile("prefetch.tensormap [%0];" :: "l"(&tm.wo));
            asm volatile("prefetch.tensormap [%0];" :: "l"(&tm.w2));
        }
        bar_init_done();
        const int e = lane >> 3, gg = lane & 7;
        const int ocol = 64 * cg + 16 * (kg >> 2) + gg + 8 * (e >> 1);
        const int orow = 2 * (kg & 3) + (e & 1);
        const __nv_bfloat16 xres = x[orow * 512 + ocol];
        if (lane == 0) {
            uint32_t due = pace.t0 + ((((cta * 37) & 127) * pace.tau) >> 7);
            #pragma unroll 1
            for (int i = 1; i < NFILL; i++) {
                const int s = i < NSLOT ? i : (i < 15 ? i - 11 : (i == 15 ? 0 : (i < 20 ? i - NSLOT : 8 + ((i - 20) >> 1))));
                if (i >= NSLOT) mbar_wait0(i < 15 ? bar_emptyA : bar_emptyK + (s == 0 ? 0 : s - 3) * 8);
                #pragma unroll 1
                for (uint32_t n = 0; n < SPIN_LIMIT && gtime32() - t_start < due; n++) {}
                if (i == 1 || i == 12 || i == 15 || i == 16) TRACE(44 + (i == 1 ? 0 : i == 12 ? 1 : i == 15 ? 2 : 3));
                const uint32_t bar = bar_full + i * 8, dst = sb + s * SLOT;
                const int tau = i >= pace.first_tail ? pace.tau_tail : pace.tau;
                if (i <= 2) {
                    mbar_expect_tx(bar, SLOT);
                    tma2d(dst, &tm.wq, cta * 32, (i - 1) * 256, bar);
                } else if (i == 3) {
                    if (cta < 112) {
                        mbar_expect_tx(bar, SLOT);
                        tma2d(dst, &tm.w1, cta * 16, 0, bar);
                        tma2d(dst + 8192, &tm.w1, cta * 16, 256, bar);
                    }
                } else if (i <= 10) {
                    mbar_expect_tx(bar, SLOT);
                    bulk_g2s(dst, kcache + ((size_t)kvrow0 + (i - 3) * 64) * 128, SLOT, bar);
                } else if (i <= 18) {
                    mbar_expect_tx(bar, SLOT);
                    tma2d(dst, &tm.v, 0, (kvrow0 + (i - 11) * 64) * 2, bar);
                } else if (i == 19) {
                    mbar_expect_tx(bar, 112 * 128);
                    tma2d(dst, &tm.w2, cg * 64, kg * 112, bar);
                } else {
                    mbar_expect_tx(bar, SLOT / 2);
                    tma2d(dst + (i & 1) * 8192, &tm.wo, cg * 64, kg * 256 + (i - 20) * 64, bar);
                }
                due += (i == 3 || i == 19) ? (tau * 7) >> 3 : (i >= 20 ? tau >> 1 : tau);
            }
            TRACE(40);
        }
        __syncwarp();
        mbar_wait0(bar_ready);
        mbar_wait0(bar_cdone);
        const uint32_t* pp = scr->part + ((size_t)(cg * 32 + e * 8) * 128 + kg * 8 + gg) * 4;
        if (lane == 0) TRACE(34);
        uint4 v[8];
        #pragma unroll
        for (int i = 0; i < 8; i++) v[i] = ld_rlx4(pp + i * 512);
        #pragma unroll 1
        for (uint32_t n = 0; ; n++) {
            bool bad = false;
            #pragma unroll
            for (int i = 0; i < 8; i++) if (has_poison(v[i])) { v[i] = ld_rlx4(pp + i * 512); bad = true; }
            if (!__any_sync(0xffffffffu, bad)) break;
            if (n > SPIN_LIMIT) __trap();
        }
        if (lane == 0) TRACE(37);
        float s0 = 0.f, s1 = 0.f, s2 = 0.f, s3 = 0.f;
        #pragma unroll
        for (int i = 0; i < 8; i++) {
            s0 += __uint_as_float(v[i].x); s1 += __uint_as_float(v[i].y);
            s2 += __uint_as_float(v[i].z); s3 += __uint_as_float(v[i].w);
        }
        {
            const bool hi = e & 2;
            float a = hi ? s0 : s2, b = hi ? s1 : s3;
            float ka = hi ? s2 : s0, kb = hi ? s3 : s1;
            ka += __shfl_xor_sync(0xffffffffu, a, 16);
            kb += __shfl_xor_sync(0xffffffffu, b, 16);
            const bool od = e & 1;
            float snd = od ? ka : kb, keep = od ? kb : ka;
            keep += __shfl_xor_sync(0xffffffffu, snd, 8);
            out[orow * 512 + ocol] = __float2bfloat16_rn(__bfloat162float(xres) + keep);
        }
        if (lane == 0) TRACE(42);
        return;
    }

    if (warp == 9) {
        const uint32_t cnt0 = ld_rlx(scr->cnt + hkv * 32);
        const uint4 pz = make_uint4(POISON, POISON, POISON, POISON);
        st_rlx4(scr->q + (lane >> 2) * 2048 + cta * 16 + (lane & 3) * 4, pz);
        if (lane < 16 && cta < 112) st_rlx4(scr->h + cta * 64 + lane * 4, pz);
        if (lane < 2) st_rlx4(scr->st + cta * 8 + lane * 4, pz);
        st_rlx4(scr->o + cta * 256 + lane * 4, pz);
        st_rlx4(scr->o + cta * 256 + 128 + lane * 4, pz);
        #pragma unroll
        for (int i = 0; i < 8; i++) st_rlx4(scr->part + ((size_t)(cg * 32 + kg * 2) * 128 + i * 32 + lane) * 4, pz);
        bar_ln_done();
        const uint32_t target = (cnt0 & ~15u) + 16u;
        if (lane == 0) {
            TRACE(11);
            asm volatile("fence.acq_rel.gpu;" ::: "memory");
            TRACE(12);
            asm volatile("red.relaxed.gpu.global.add.u32 [%0], 1;" :: "l"(scr->cnt + hkv * 32) : "memory");
            #pragma unroll 1
            for (uint32_t n = 0; (int32_t)(ld_acq(scr->cnt + hkv * 32) - target) < 0; n++) if (n > SPIN_LIMIT) __trap();
            TRACE(3);
        }
        __syncwarp();
        {
            const uint32_t* pq = scr->q + bb * 2048 + hkv * 256 + lane * 4;
            uint4 v0, v1;
            #pragma unroll 1
            for (uint32_t n = 0; ; n++) {
                v0 = ld_rlx4(pq); v1 = ld_rlx4(pq + 128);
                if (!__any_sync(0xffffffffu, has_poison(v0) || has_poison(v1))) break;
                if (n > SPIN_LIMIT) __trap();
            }
            const uint32_t a = sb + SM_Q + (lane >> 4) * 272 + (lane & 15) * 16;
            sts128(a, v0); sts128(a + 544, v1);
            __syncwarp();
            if (lane == 0) { mbar_arrive(bar_q); TRACE(23); }
        }
        #pragma unroll 1
        for (uint32_t n = 0; __any_sync(0xffffffffu, (int32_t)(ld_acq(scr->cnt + (lane & 7) * 32) - target) < 0); n++)
            if (n > SPIN_LIMIT) __trap();
        if (lane == 0) { mbar_arrive(bar_ready); TRACE(20); }
        mbar_wait0(bar_full + 12 * 8);
        {
            const uint32_t* p3 = lane < 16 ? scr->h + kg * 448 + 384 + lane * 4 : scr->st + (cta ^ 1) * 8 + (lane & 1) * 4;
            uint4 v[4];
            #pragma unroll 1
            for (uint32_t n = 0; ; n++) {
                #pragma unroll
                for (int i = 0; i < 3; i++) v[i] = ld_rlx4(scr->h + kg * 448 + i * 128 + lane * 4);
                v[3] = ld_rlx4(p3);
                if (!__any_sync(0xffffffffu, has_poison(v[0]) || has_poison(v[1]) || has_poison(v[2]) || has_poison(v[3]))) break;
                if (n > SPIN_LIMIT) __trap();
            }
            #pragma unroll
            for (int i = 0; i < 3; i++) sts128(sb + SM_H + i * 512 + lane * 16, v[i]);
            if (lane < 18) sts128(lane < 16 ? sb + SM_H + 1536 + lane * 16 : sb + SM_ST + (lane & 1) * 16, v[3]);
        }
        __syncwarp();
        if (lane == 0) { mbar_arrive(bar_st); TRACE(32); }
        return;
    }

    const uint4 xa = *reinterpret_cast<const uint4*>(x + warp * 512 + lane * 8);
    const uint4 xb = *reinterpret_cast<const uint4*>(x + warp * 512 + 256 + lane * 8);
    if (lane == 0) {
        #pragma unroll 1
        for (int j = 1 + warp; j < NBAR; j += 8) mbar_init(bar_full + j * 8, bar_full + j * 8 == bar_cdone ? 8 : 1);
        mbar_fence_init();
    }
    bar_init_done();
    if (tid == 0) TRACE(13);
    {
        float xv[16];
        const uint32_t xw[8] = {xa.x, xa.y, xa.z, xa.w, xb.x, xb.y, xb.z, xb.w};
        #pragma unroll
        for (int i = 0; i < 8; i++) { xv[2 * i] = bf_lo(xw[i]); xv[2 * i + 1] = bf_hi(xw[i]); }
        float s = 0.f;
        #pragma unroll
        for (int i = 0; i < 16; i++) s += xv[i];
        #pragma unroll
        for (int o = 16; o; o >>= 1) s += __shfl_xor_sync(0xffffffffu, s, o);
        const float mean = s * (1.f / 512.f);
        if (tid == 0) TRACE(14);
        float q = 0.f;
        #pragma unroll
        for (int i = 0; i < 16; i++) { const float d = xv[i] - mean; q += d * d; }
        #pragma unroll
        for (int o = 16; o; o >>= 1) q += __shfl_xor_sync(0xffffffffu, q, o);
        const float mb = bf16r(mean);
        const float den = bf16r(sqrt_approx(bf16r(bf16r(q * (1.f / 512.f)) + 1e-5f)));
        uint32_t o[8];
        #pragma unroll
        for (int i = 0; i < 8; i++)
            o[i] = pack_bf16(__fdividef(bf16r(xv[2 * i] - mb), den), __fdividef(bf16r(xv[2 * i + 1] - mb), den));
        sts128(sb + SM_XN + warp * 1040 + lane * 16, make_uint4(o[0], o[1], o[2], o[3]));
        sts128(sb + SM_XN + warp * 1040 + 512 + lane * 16, make_uint4(o[4], o[5], o[6], o[7]));
    }
    if (tid == 0) TRACE(15);
    bar_ln_done();
    if (tid == 0) TRACE(0);

    {
        uint32_t xf[4][2];
        #pragma unroll
        for (int s = 0; s < 4; s++) {
            const uint32_t a = sb + SM_XN + g * 1040 + (warp * 64 + s * 16 + 2 * t) * 2;
            xf[s][0] = lds32(a); xf[s][1] = lds32(a + 16);
        }
        float acc[3][4] = {};
        const int mi = lane >> 3, rr = lane & 7;
        const int krow = (warp & 3) * 64 + (mi >> 1) * 8 + rr;
        mbar_wait0(bar_full + (1 + (warp >> 2)) * 8);
        if (tid == 0) TRACE(16);
        if (tid == 128) TRACE(17);
        #pragma unroll
        for (int s = 0; s < 4; s++) {
            const int r = krow + s * 16;
            #pragma unroll
            for (int mt = 0; mt < 2; mt++) {
                uint32_t a[4];
                ldsm_x4_t(a, sb + (1 + (warp >> 2)) * SLOT + r * 64 + (((2 * mt + (mi & 1)) ^ ((r >> 1) & 3)) << 4));
                mma16816(acc[mt], a[0], a[1], a[2], a[3], xf[s][0], xf[s][1]);
            }
        }
        if (cta < 112) {
            mbar_wait0(bar_full + 3 * 8);
            if (tid == 0) TRACE(18);
            #pragma unroll
            for (int s = 0; s < 4; s++) {
                const int r = (warp >> 2) * 256 + krow + s * 16;
                uint32_t a[4];
                ldsm_x4_t(a, sb + 3 * SLOT + r * 32 + (((mi & 1) ^ ((r >> 2) & 1)) << 4));
                mma16816(acc[2], a[0], a[1], a[2], a[3], xf[s][0], xf[s][1]);
            }
        }
        #pragma unroll
        for (int mt = 0; mt < 3; mt++)
            sts128(sb + SM_RED + (warp * 3 + mt) * 512 + lane * 16,
                   make_uint4(__float_as_uint(acc[mt][0]), __float_as_uint(acc[mt][1]), __float_as_uint(acc[mt][2]), __float_as_uint(acc[mt][3])));
    }
    bar_consumers();
    if (tid == 0) { TRACE(1); mbar_arrive(bar_emptyA); }
    if (tid < 192) {
        const int tile = tid < 128 ? ((tid >> 3) & 1) : 2;
        const int b = tid < 128 ? (tid >> 4) : ((tid - 128) >> 3);
        const int j = tid & 7;
        const uint32_t a = sb + SM_RED + tile * 512 + (4 * ((2 * j) & 7) + (b >> 1)) * 16 + (2 * (j >> 2) + (b & 1)) * 4;
        float v0 = 0.f, v1 = 0.f;
        #pragma unroll
        for (int w = 0; w < 8; w++) { v0 += lds32f(a + w * 1536); v1 += lds32f(a + w * 1536 + 64); }
        if (tid < 128) {
            st_rlx(scr->q + b * 2048 + cta * 16 + (tid & 15), unpoison(pack_bf16(v0, v1)));
        } else if (cta < 112) {
            v0 = bf16r(v0); v1 = bf16r(v1);
            v0 = __fdividef(v0, 1.f + __expf(-v0));
            v1 = __fdividef(v1, 1.f + __expf(-v1));
            st_rlx(scr->h + cta * 64 + b * 8 + 2 * (j & 3) + (j >> 2), unpoison(pack_bf16(v0, v1)));
        }
    }
    if (tid == 0) TRACE(2);

    float sc[4][4] = {};
    {
        uint4 qf[4];
        mbar_wait0(bar_q);
        #pragma unroll
        for (int j = 0; j < 4; j++) qf[j] = lds128(sb + SM_Q + (g & 3) * 272 + (4 * (j ^ (g >> 2)) + t) * 16);
        const int fill = warp == 0 ? 0 : warp + 3;
        mbar_wait0(bar_full + fill * 8);
        if (tid == 0 && qf[3].w != 0x12345) TRACE(19);
        const uint32_t kb = sb + fill * SLOT + g * 256 + t * 16;
        #pragma unroll
        for (int j = 0; j < 4; j++) {
            #pragma unroll
            for (int mt = 0; mt < 4; mt++) {
                const uint32_t a = kb + mt * 4096 + ((j ^ (g & 1)) << 6);
                const uint4 lo = lds128(a), hi = lds128(a + 2048);
                mma16816(sc[mt], lo.x, hi.x, lo.y, hi.y, qf[j].x, qf[j].y);
                mma16816(sc[mt], lo.z, hi.z, lo.w, hi.w, qf[j].z, qf[j].w);
            }
        }
        __syncwarp();
        if (lane == 0 && warp < 7) mbar_arrive(bar_emptyK + warp * 8);
    }
    if (tid == 0) TRACE(4);
    if (tid == 224) TRACE(5);
    const bool valid = (t >> 1) == (g & 1);
    const int h0 = 2 * (t & 1);
    {
        float m0 = -INFINITY, m1 = -INFINITY;
        #pragma unroll
        for (int mt = 0; mt < 4; mt++) {
            #pragma unroll
            for (int i = 0; i < 4; i++) sc[mt][i] = bf16r(bf16r(sc[mt][i]) * 0.08838834764831845f);
            m0 = fmaxf(m0, fmaxf(sc[mt][0], sc[mt][2]));
            m1 = fmaxf(m1, fmaxf(sc[mt][1], sc[mt][3]));
        }
        if (!valid) { m0 = -INFINITY; m1 = -INFINITY; }
        #pragma unroll
        for (int o = 2; o <= 16; o <<= 1) {
            m0 = fmaxf(m0, __shfl_xor_sync(0xffffffffu, m0, o));
            m1 = fmaxf(m1, __shfl_xor_sync(0xffffffffu, m1, o));
        }
        if (lane < 2) { sts32f(sb + SM_WMAX + warp * 16 + h0 * 4, m0); sts32f(sb + SM_WMAX + warp * 16 + h0 * 4 + 4, m1); }
    }
    bar_consumers();
    if (tid == 0) TRACE(21);
    float mloc0 = -INFINITY, mloc1 = -INFINITY;
    {
        #pragma unroll
        for (int w = 0; w < 8; w++) {
            mloc0 = fmaxf(mloc0, lds32f(sb + SM_WMAX + w * 16 + h0 * 4));
            mloc1 = fmaxf(mloc1, lds32f(sb + SM_WMAX + w * 16 + h0 * 4 + 4));
        }
        const float L2E = 1.4426950408889634f;
        float l0 = 0.f, l1 = 0.f;
        const uint32_t pa = sb + SM_P + (h0 * 260 + warp * 32 + (g & 3) * 8 + (g >> 2)) * 4;
        #pragma unroll
        for (int mt = 0; mt < 4; mt++) {
            const float p0 = ex2((sc[mt][0] - mloc0) * L2E), p2 = ex2((sc[mt][2] - mloc0) * L2E);
            const float p1 = ex2((sc[mt][1] - mloc1) * L2E), p3 = ex2((sc[mt][3] - mloc1) * L2E);
            l0 += p0 + p2; l1 += p1 + p3;
            if (valid) { sts32(pa + mt * 8, pack_bf16(p0, p2)); sts32(pa + 1040 + mt * 8, pack_bf16(p1, p3)); }
        }
        if (!valid) { l0 = 0.f; l1 = 0.f; }
        #pragma unroll
        for (int o = 2; o <= 16; o <<= 1) {
            l0 += __shfl_xor_sync(0xffffffffu, l0, o);
            l1 += __shfl_xor_sync(0xffffffffu, l1, o);
        }
        if (lane < 2) { sts32f(sb + SM_WSUM + warp * 16 + h0 * 4, l0); sts32f(sb + SM_WSUM + warp * 16 + h0 * 4 + 4, l1); }
    }
    if (tid == 0) TRACE(22);
    const int mtC = warp & 3, kh = warp >> 2;
    bar_consumers();
    if (tid == 0) TRACE(6);
    float lloc0 = 0.f, lloc1 = 0.f;
    #pragma unroll
    for (int w = 0; w < 8; w++) {
        lloc0 += lds32f(sb + SM_WSUM + w * 16 + h0 * 4);
        lloc1 += lds32f(sb + SM_WSUM + w * 16 + h0 * 4 + 4);
    }
    if (tid < 2) {
        st_rlx(scr->st + cta * 8 + h0, unpoison(__float_as_uint(mloc0)));
        st_rlx(scr->st + cta * 8 + h0 + 1, unpoison(__float_as_uint(mloc1)));
        st_rlx(scr->st + cta * 8 + 4 + h0, unpoison(__float_as_uint(lloc0)));
        st_rlx(scr->st + cta * 8 + 4 + h0 + 1, unpoison(__float_as_uint(lloc1)));
    }

    float oa[2][4] = {};
    float scale0 = 0.f, scale1 = 0.f;
    {
        const int mi = lane >> 3, rr = lane & 7;
        const int key = (rr >> 1) + 4 * (mi >> 1) + 8 * (rr & 1);
        const int rowp = 2 * key + (warp >> 2);
        const uint32_t voff = rowp * 128 + (((2 * (warp & 3) + (mi & 1)) ^ (rowp & 7)) << 4);
        #pragma unroll 1
        for (int vc = 0; vc < 8; vc++) {
            uint4 p0 = make_uint4(0u, 0u, 0u, 0u), p1 = p0;
            if (g < 4) {
                const uint32_t a = sb + SM_P + (g * 260 + vc * 32 + t * 8) * 4;
                p0 = lds128(a); p1 = lds128(a + 16);
            }
            if (vc == 7) {
                mbar_wait0(bar_st);
                const float L2E = 1.4426950408889634f;
                const float mo0 = lds32f(sb + SM_ST + h0 * 4), mo1 = lds32f(sb + SM_ST + h0 * 4 + 4);
                const float mg0 = fmaxf(mloc0, mo0), mg1 = fmaxf(mloc1, mo1);
                const float e0 = ex2((mloc0 - mg0) * L2E), e1 = ex2((mloc1 - mg1) * L2E);
                scale0 = __fdividef(e0, lloc0 * e0 + lds32f(sb + SM_ST + 16 + h0 * 4) * ex2((mo0 - mg0) * L2E));
                scale1 = __fdividef(e1, lloc1 * e1 + lds32f(sb + SM_ST + 20 + h0 * 4) * ex2((mo1 - mg1) * L2E));
            }
            const int fill = 11 + vc, slot = vc == 0 ? 11 : (vc < 4 ? vc : (vc == 4 ? 0 : vc - 1));
            mbar_wait0(bar_full + fill * 8);
            if (tid == 0) TRACE(24 + vc);
            const uint32_t vb = sb + slot * SLOT + voff;
            uint32_t a0[4], a1[4], a2[4], a3[4];
            ldsm_x4_t(a0, vb); ldsm_x4_t(a1, vb + 4096); ldsm_x4_t(a2, vb + 8192); ldsm_x4_t(a3, vb + 12288);
            mma16816(oa[0], a0[0], a0[1], a0[2], a0[3], p0.x, p0.y);
            mma16816(oa[1], a1[0], a1[1], a1[2], a1[3], p0.z, p0.w);
            mma16816(oa[0], a2[0], a2[1], a2[2], a2[3], p1.x, p1.y);
            mma16816(oa[1], a3[0], a3[1], a3[2], a3[3], p1.z, p1.w);
        }
        if (tid == 0) TRACE(7);
        const uint32_t lo = pack_bf16((oa[0][0] + oa[1][0]) * scale0, (oa[0][1] + oa[1][1]) * scale1);
        const uint32_t hi = pack_bf16((oa[0][2] + oa[1][2]) * scale0, (oa[0][3] + oa[1][3]) * scale1);
        const bool odd = g & 1;
        const uint32_t y = __shfl_xor_sync(0xffffffffu, odd ? lo : hi, 4);
        const uint32_t first = odd ? y : lo, second = odd ? hi : y;
        if (t < 2) {
            uint32_t* po = scr->o + cta * 256 + h0 * 64 + (warp >> 1) * 16 + (g >> 1) * 4 + (warp & 1) * 2 + (g & 1);
            st_rlx(po, unpoison(__byte_perm(first, second, 0x5410)));
            st_rlx(po + 64, unpoison(__byte_perm(first, second, 0x7632)));
        }
        if (tid == 0) TRACE(49);
    }

    {
        float acc[4][4] = {};
        const int mi = lane >> 3, rr = lane & 7;
        const int wrow = (mi >> 1) * 8 + rr;
        const uint32_t woff = wrow * 128 + (((2 * mtC + (mi & 1)) ^ rr) << 4);
        mbar_wait0(bar_full + 19 * 8);
        if (tid == 0) TRACE(8);
        const uint32_t* po = scr->o + (hkv * 16 + warp * 2) * 256 + (kg & 1) * 128 + lane * 4;
        uint4 v0 = ld_rlx4(po), v1 = ld_rlx4(po + 256);
        #pragma unroll
        for (int i = 0; i < 4; i++) {
            if (kh * 4 + i < 7) {
                uint32_t a[4];
                ldsm_x4_t(a, sb + 7 * SLOT + (kh * 4 + i) * 2048 + woff);
                const uint32_t ha = sb + SM_H + (kh * 4 + i) * 256 + lane * 8;
                mma16816(acc[i & 1], a[0], a[1], a[2], a[3], lds32(ha), lds32(ha + 4));
            }
        }
        #pragma unroll 1
        for (uint32_t n = 0; ; n++) {
            const bool b0 = __any_sync(0xffffffffu, has_poison(v0)), b1 = __any_sync(0xffffffffu, has_poison(v1));
            if (!b0 && !b1) break;
            if (b0) v0 = ld_rlx4(po);
            if (b1) v1 = ld_rlx4(po + 256);
            if (n > SPIN_LIMIT) __trap();
        }
        sts128(sb + SM_O + warp * 1088 + lane * 16, v0);
        sts128(sb + SM_O + warp * 1088 + 544 + lane * 16, v1);
        bar_consumers();
        if (tid == 0) { TRACE(9); TRACE(48); }
        uint4 of[2][2][2];
        #pragma unroll
        for (int i = 0; i < 8; i++)
            of[i >> 2][(i >> 1) & 1][i & 1] = lds128(sb + SM_O + (2 * g + ((i >> 1) & 1)) * 544 + (i >> 2) * 256 + ((i & 1) * 2 + kh) * 64 + t * 16);
        #pragma unroll
        for (int pc = 0; pc < 4; pc++) {
            mbar_wait0(bar_full + (20 + pc) * 8);
            const uint32_t wb = sb + 8 * SLOT + pc * 8192 + kh * 4096 + woff;
            uint32_t a0[4], a1[4];
            ldsm_x4_t(a0, wb); ldsm_x4_t(a1, wb + 2048);
            const uint4 u = of[pc >> 1][0][pc & 1], w = of[pc >> 1][1][pc & 1];
            mma16816(acc[0], a0[0], a0[1], a0[2], a0[3], u.x, u.y);
            mma16816(acc[1], a1[0], a1[1], a1[2], a1[3], u.z, u.w);
            mma16816(acc[2], a0[0], a0[1], a0[2], a0[3], w.x, w.y);
            mma16816(acc[3], a1[0], a1[1], a1[2], a1[3], w.z, w.w);
        }
        #pragma unroll
        for (int i = 0; i < 4; i++) { acc[0][i] += acc[2][i]; acc[1][i] += acc[3][i]; }
        st_rlx4(scr->part + ((size_t)(cg * 32 + kg * 2 + kh) * 128 + mtC * 32 + t * 8 + g) * 4,
                make_uint4(unpoison(__float_as_uint(acc[0][0] + acc[1][0])), unpoison(__float_as_uint(acc[0][1] + acc[1][1])),
                           unpoison(__float_as_uint(acc[0][2] + acc[1][2])), unpoison(__float_as_uint(acc[0][3] + acc[1][3]))));
        __syncwarp();
        if (lane == 0) mbar_arrive(bar_cdone);
        if (tid == 0) TRACE(10);
    }
}

typedef CUresult (*EncodeTiledFn)(CUtensorMap*, CUtensorMapDataType, cuuint32_t, void*, const cuuint64_t*, const cuuint64_t*,
                                  const cuuint32_t*, const cuuint32_t*, CUtensorMapInterleave, CUtensorMapSwizzle,
                                  CUtensorMapL2promotion, CUtensorMapFloatOOBfill);

void make_map(EncodeTiledFn enc, CUtensorMap* m, const void* base, uint64_t cols, uint64_t rows, uint32_t box_cols,
              uint32_t box_rows, CUtensorMapSwizzle sw) {
    cuuint64_t gd[2] = {cols, rows};
    cuuint64_t gs[1] = {cols * 2};
    cuuint32_t bd[2] = {box_cols, box_rows};
    cuuint32_t es[2] = {1, 1};
    enc(m, CU_TENSOR_MAP_DATA_TYPE_BFLOAT16, 2, const_cast<void*>(base), gd, gs, bd, es, CU_TENSOR_MAP_INTERLEAVE_NONE, sw,
        CU_TENSOR_MAP_L2_PROMOTION_L2_256B, CU_TENSOR_MAP_FLOAT_OOB_FILL_NONE);
}

}

extern "C" void kernel_launch(void* const* d_in, const int* in_sizes, int n_in, void* d_out, int out_size) {
    (void)in_sizes; (void)n_in; (void)out_size;
    static EncodeTiledFn enc = nullptr;
    static Scratch* scr = nullptr;
    if (!enc) {
        cudaGetSymbolAddress((void**)&scr, g_scratch);
        void* fn = nullptr;
        cudaDriverEntryPointQueryResult qr;
        cudaGetDriverEntryPoint("cuTensorMapEncodeTiled", &fn, cudaEnableDefault, &qr);
        enc = (EncodeTiledFn)fn;
        cudaFuncSetAttribute(fused_decode_kernel, cudaFuncAttributeMaxDynamicSharedMemorySize, SMEM_BYTES);
    }
    TMaps tm;
    make_map(enc, &tm.wq, d_in[3], 4096, 512, 32, 256, CU_TENSOR_MAP_SWIZZLE_64B);
    make_map(enc, &tm.w1, d_in[6], 1792, 512, 16, 256, CU_TENSOR_MAP_SWIZZLE_32B);
    make_map(enc, &tm.v, d_in[2], 64, 8ull * 8 * 4096 * 2, 64, 128, CU_TENSOR_MAP_SWIZZLE_128B);
    make_map(enc, &tm.wo, d_in[4], 512, 4096, 64, 64, CU_TENSOR_MAP_SWIZZLE_128B);
    make_map(enc, &tm.w2, d_in[7], 512, 1792, 64, 112, CU_TENSOR_MAP_SWIZZLE_128B);
    fused_decode_kernel<<<NCTA, NTHREADS, SMEM_BYTES, cudaStreamPerThread>>>(
        (const __nv_bfloat16*)d_in[1], (const __nv_bfloat16*)d_in[0], (__nv_bfloat16*)d_out, scr, g_pace, tm);
}
```

```cpp
#include <cuda_runtime.h>
#include <cuda_bf16.h>
#include <cuda.h>
#include <stdint.h>

namespace {

constexpr int NCTA = 128;
constexpr int NTHREADS = 320;
constexpr int SLOT = 16384;
constexpr int NSLOT = 12;
constexpr int NFILL = 24;
constexpr uint32_t POISON = 0xFFFFFFFFu;
constexpr uint32_t SPIN_LIMIT = 1u << 22;

struct Pace { int t0, tau, tau_tail, first_tail, opoll; };
constexpr Pace g_pace = {100, 640, 640, 19, 20};

constexpr int SM_RING = 0;
constexpr int SM_XN = NSLOT * SLOT;
constexpr int SM_RED = SM_XN + 8 * 1040;
constexpr int SM_P = SM_RED + 8 * 3 * 512;
constexpr int SM_WMAX = SM_P + 4 * 260 * 4;
constexpr int SM_WSUM = SM_WMAX + 128;
constexpr int SM_ST = SM_WSUM + 128;
constexpr int SM_Q = SM_ST + 32;
constexpr int SM_H = SM_Q + 4 * 272;
constexpr int SM_O = SM_RED;
constexpr int SM_PAIR = SM_RED + 16 * 544;
constexpr int SM_BAR = SM_H + 7 * 256;
constexpr int NBAR = NFILL + 7 + 3;
constexpr int SM_TOTAL = SM_BAR + NBAR * 8;
constexpr int SMEM_BYTES = SM_TOTAL + 1024;

struct TMaps { CUtensorMap wq, w1, v, wo, w2; };

struct Scratch {
    float acc[8 * 4 * 2 * 128];
    uint32_t o[NCTA * 256];
    uint32_t q[8 * 2048];
    uint32_t h[112 * 64];
    uint32_t st[NCTA * 8];
    uint32_t cnt[8 * 32];
};
__device__ __align__(128) Scratch g_scratch;

#define TRACE(i) do {} while (0)

__device__ __forceinline__ uint32_t clk32() { uint32_t c; asm volatile("mov.u32 %0, %clock;" : "=r"(c)); return c; }
__device__ __forceinline__ uint32_t gtime32() { uint32_t c; asm volatile("mov.u32 %0, %globaltimer_lo;" : "=r"(c)); return c; }
__device__ __forceinline__ uint32_t smem_u32(const void* p) { return (uint32_t)__cvta_generic_to_shared(p); }

__device__ __forceinline__ void mbar_init(uint32_t bar, uint32_t cnt) {
    asm volatile("mbarrier.init.shared::cta.b64 [%0], %1;" :: "r"(bar), "r"(cnt) : "memory");
}
__device__ __forceinline__ void mbar_fence_init() { asm volatile("fence.mbarrier_init.release.cluster;" ::: "memory"); }
__device__ __forceinline__ void mbar_expect_tx(uint32_t bar, uint32_t bytes) {
    asm volatile("mbarrier.arrive.expect_tx.shared::cta.b64 _, [%0], %1;" :: "r"(bar), "r"(bytes) : "memory");
}
__device__ __forceinline__ void mbar_arrive(uint32_t bar) {
    asm volatile("mbarrier.arrive.shared::cta.b64 _, [%0];" :: "r"(bar) : "memory");
}
__device__ __forceinline__ void mbar_wait0(uint32_t bar) {
    #pragma unroll 1
    for (uint32_t i = 0; i < SPIN_LIMIT; i++) {
        uint32_t ok;
        asm volatile("{\n.reg .pred p;\nmbarrier.try_wait.parity.shared::cta.b64 p, [%1], 0;\nselp.u32 %0, 1, 0, p;\n}"
                     : "=r"(ok) : "r"(bar) : "memory");
        if (ok) return;
    }
    __trap();
}
constexpr uint64_t EVICT_FIRST = 0x12F0000000000000ull;
__device__ __forceinline__ void bulk_g2s(uint32_t dst, const void* src, uint32_t bytes, uint32_t bar) {
    asm volatile("cp.async.bulk.shared::cluster.global.mbarrier::complete_tx::bytes.L2::cache_hint [%0], [%1], %2, [%3], %4;"
                 :: "r"(dst), "l"(src), "r"(bytes), "r"(bar), "l"(EVICT_FIRST) : "memory");
}
__device__ __forceinline__ void tma2d(uint32_t dst, const CUtensorMap* tm, int c0, int c1, uint32_t bar) {
    asm volatile("cp.async.bulk.tensor.2d.shared::cluster.global.mbarrier::complete_tx::bytes.L2::cache_hint [%0], [%1, {%3, %4}], [%2], %5;"
                 :: "r"(dst), "l"(tm), "r"(bar), "r"(c0), "r"(c1), "l"(EVICT_FIRST) : "memory");
}
__device__ __forceinline__ void bar_consumers() { asm volatile("bar.sync 1, 256;" ::: "memory"); }
__device__ __forceinline__ void bar_init_done() { asm volatile("bar.sync 2, 288;" ::: "memory"); }
__device__ __forceinline__ void bar_ln_done() { asm volatile("bar.sync 3, 288;" ::: "memory"); }

__device__ __forceinline__ uint4 lds128(uint32_t a) {
    uint4 v; asm volatile("ld.shared.v4.u32 {%0,%1,%2,%3}, [%4];" : "=r"(v.x), "=r"(v.y), "=r"(v.z), "=r"(v.w) : "r"(a)); return v;
}
__device__ __forceinline__ uint32_t lds32(uint32_t a) { uint32_t v; asm volatile("ld.shared.u32 %0, [%1];" : "=r"(v) : "r"(a)); return v; }
__device__ __forceinline__ float lds32f(uint32_t a) { float v; asm volatile("ld.shared.f32 %0, [%1];" : "=f"(v) : "r"(a)); return v; }
__device__ __forceinline__ void sts32(uint32_t a, uint32_t v) { asm volatile("st.shared.u32 [%0], %1;" :: "r"(a), "r"(v) : "memory"); }
__device__ __forceinline__ void sts32f(uint32_t a, float v) { asm volatile("st.shared.f32 [%0], %1;" :: "r"(a), "f"(v) : "memory"); }
__device__ __forceinline__ void sts128(uint32_t a, uint4 v) {
    asm volatile("st.shared.v4.u32 [%0], {%1,%2,%3,%4};" :: "r"(a), "r"(v.x), "r"(v.y), "r"(v.z), "r"(v.w) : "memory");
}
__device__ __forceinline__ void ldsm_x4_t(uint32_t (&r)[4], uint32_t a) {
    asm volatile("ldmatrix.sync.aligned.m8n8.x4.trans.shared.b16 {%0,%1,%2,%3}, [%4];"
                 : "=r"(r[0]), "=r"(r[1]), "=r"(r[2]), "=r"(r[3]) : "r"(a));
}
__device__ __forceinline__ void mma16816(float (&c)[4], uint32_t a0, uint32_t a1, uint32_t a2, uint32_t a3, uint32_t b0, uint32_t b1) {
    asm volatile("mma.sync.aligned.m16n8k16.row.col.f32.bf16.bf16.f32 {%0,%1,%2,%3}, {%4,%5,%6,%7}, {%8,%9}, {%0,%1,%2,%3};"
                 : "+f"(c[0]), "+f"(c[1]), "+f"(c[2]), "+f"(c[3]) : "r"(a0), "r"(a1), "r"(a2), "r"(a3), "r"(b0), "r"(b1));
}

__device__ __forceinline__ uint32_t ld_rlx(const uint32_t* p) {
    uint32_t v; asm volatile("ld.relaxed.gpu.global.u32 %0, [%1];" : "=r"(v) : "l"(p) : "memory"); return v;
}
__device__ __forceinline__ uint32_t ld_acq(const uint32_t* p) {
    uint32_t v; asm volatile("ld.acquire.gpu.global.u32 %0, [%1];" : "=r"(v) : "l"(p) : "memory"); return v;
}
__device__ __forceinline__ uint2 ld_rlx2(const uint32_t* p) {
    uint2 v; asm volatile("ld.relaxed.gpu.global.v2.u32 {%0,%1}, [%2];" : "=r"(v.x), "=r"(v.y) : "l"(p) : "memory"); return v;
}
__device__ __forceinline__ uint4 ld_rlx4(const uint32_t* p) {
    uint4 v; asm volatile("ld.relaxed.gpu.global.v4.u32 {%0,%1,%2,%3}, [%4];" : "=r"(v.x), "=r"(v.y), "=r"(v.z), "=r"(v.w) : "l"(p) : "memory"); return v;
}
__device__ __forceinline__ void st_rlx(uint32_t* p, uint32_t v) {
    asm volatile("st.relaxed.gpu.global.u32 [%0], %1;" :: "l"(p), "r"(v) : "memory");
}
__device__ __forceinline__ void st_rlx4(uint32_t* p, uint4 v) {
    asm volatile("st.relaxed.gpu.global.v4.u32 [%0], {%1,%2,%3,%4};" :: "l"(p), "r"(v.x), "r"(v.y), "r"(v.z), "r"(v.w) : "memory");
}
__device__ __forceinline__ bool has_poison(const uint4& v) {
    return v.x == POISON || v.y == POISON || v.z == POISON || v.w == POISON;
}
__device__ __forceinline__ uint32_t unpoison(uint32_t w) { return w == POISON ? 0x7FFFFFFFu : w; }

__device__ __forceinline__ float sqrt_approx(float x) { float r; asm("sqrt.approx.f32 %0, %1;" : "=f"(r) : "f"(x)); return r; }
__device__ __forceinline__ float ex2(float x) { float r; asm("ex2.approx.f32 %0, %1;" : "=f"(r) : "f"(x)); return r; }
__device__ __forceinline__ float bf16r(float x) { return __bfloat162float(__float2bfloat16_rn(x)); }
__device__ __forceinline__ uint32_t pack_bf16(float lo, float hi) {
    uint32_t r; asm("cvt.rn.bf16x2.f32 %0, %1, %2;" : "=r"(r) : "f"(hi), "f"(lo)); return r;
}
__device__ __forceinline__ float bf_lo(uint32_t w) { return __uint_as_float(w << 16); }
__device__ __forceinline__ float bf_hi(uint32_t w) { return __uint_as_float(w & 0xFFFF0000u); }

__global__ void __launch_bounds__(NTHREADS, 1)
fused_decode_kernel(const __nv_bfloat16* __restrict__ kcache, const __nv_bfloat16* __restrict__ x,
                    __nv_bfloat16* __restrict__ out, Scratch* __restrict__ scr, const Pace pace,
                    const __grid_constant__ TMaps tm)
{
    extern __shared__ uint8_t smem_raw[];
    const uint32_t sb = (smem_u32(smem_raw) + 1023u) & ~1023u;
    const int tid = threadIdx.x, warp = tid >> 5, lane = tid & 31;
    const int cta = blockIdx.x;
    const int hkv = cta >> 4, bb = (cta >> 1) & 7, half = cta & 1;
    const int kg = cta >> 3, cg = cta & 7;
    const int g = lane >> 2, t = lane & 3;
    const uint32_t bar_full = sb + SM_BAR, bar_emptyK = bar_full + NFILL * 8, bar_emptyA = bar_emptyK + 7 * 8;
    const uint32_t bar_q = bar_emptyA + 8, bar_st = bar_q + 8;
    const int kvrow0 = (bb * 8 + hkv) * 4096 + 3072 + half * 512;

    uint32_t t_start = 0;
    if (tid == 256) {
        mbar_init(bar_full, 1);
        mbar_fence_init();
        mbar_expect_tx(bar_full, SLOT);
        bulk_g2s(sb, kcache + (size_t)kvrow0 * 128, SLOT, bar_full);
        t_start = gtime32();
        TRACE(43);
    }

    if (warp == 8) {
        if (lane == 0) {
            asm volatile("prefetch.tensormap [%0];" :: "l"(&tm.wq));
            asm volatile("prefetch.tensormap [%0];" :: "l"(&tm.w1));
            asm volatile("prefetch.tensormap [%0];" :: "l"(&tm.v));
            asm volatile("prefetch.tensormap [%0];" :: "l"(&tm.wo));
            asm volatile("prefetch.tensormap [%0];" :: "l"(&tm.w2));
        }
        bar_init_done();
        if (lane == 0) {
            uint32_t due = pace.t0 + ((((cta * 37) & 127) * pace.tau) >> 7);
            #pragma unroll 1
            for (int i = 1; i < NFILL; i++) {
                const int s = i < NSLOT ? i : (i < 15 ? i - 11 : (i == 15 ? 0 : (i < 20 ? i - NSLOT : 8 + ((i - 20) >> 1))));
                if (i >= NSLOT) mbar_wait0(i < 15 ? bar_emptyA : bar_emptyK + (s == 0 ? 0 : s - 3) * 8);
                #pragma unroll 1
                for (uint32_t n = 0; n < SPIN_LIMIT && gtime32() - t_start < due; n++) {}
                const uint32_t bar = bar_full + i * 8, dst = sb + s * SLOT;
                const int tau = i >= pace.first_tail ? pace.tau_tail : pace.tau;
                if (i <= 2) {
                    mbar_expect_tx(bar, SLOT);
                    tma2d(dst, &tm.wq, cta * 32, (i - 1) * 256, bar);
                } else if (i == 3) {
                    if (cta < 112) {
                        mbar_expect_tx(bar, SLOT);
                        tma2d(dst, &tm.w1, cta * 16, 0, bar);
                        tma2d(dst + 8192, &tm.w1, cta * 16, 256, bar);
                    }
                } else if (i <= 10) {
                    mbar_expect_tx(bar, SLOT);
                    bulk_g2s(dst, kcache + ((size_t)kvrow0 + (i - 3) * 64) * 128, SLOT, bar);
                } else if (i <= 18) {
                    mbar_expect_tx(bar, SLOT);
                    tma2d(dst, &tm.v, 0, (kvrow0 + (i - 11) * 64) * 2, bar);
                } else if (i == 19) {
                    mbar_expect_tx(bar, 112 * 128);
                    tma2d(dst, &tm.w2, cg * 64, kg * 112, bar);
                } else {
                    mbar_expect_tx(bar, SLOT / 2);
                    tma2d(dst + (i & 1) * 8192, &tm.wo, cg * 64, kg * 256 + (i - 20) * 64, bar);
                }
                due += (i == 3 || i == 19) ? (tau * 7) >> 3 : (i >= 20 ? tau >> 1 : tau);
            }
            TRACE(40);
        }
        return;
    }

    if (warp == 9) {
        const uint32_t cnt0 = ld_rlx(scr->cnt + hkv * 32);
        const uint4 pz = make_uint4(POISON, POISON, POISON, POISON);
        st_rlx4(scr->q + (lane >> 2) * 2048 + cta * 16 + (lane & 3) * 4, pz);
        if (lane < 16 && cta < 112) st_rlx4(scr->h + cta * 64 + lane * 4, pz);
        if (lane < 2) st_rlx4(scr->st + cta * 8 + lane * 4, pz);
        st_rlx4(scr->o + cta * 256 + lane * 4, pz);
        st_rlx4(scr->o + cta * 256 + 128 + lane * 4, pz);
        if (lane < 16) st_rlx4(reinterpret_cast<uint32_t*>(scr->acc) + cta * 64 + lane * 4, make_uint4(0u, 0u, 0u, 0u));
        bar_ln_done();
        const uint32_t target = (cnt0 & ~15u) + 16u;
        if (lane == 0) {
            TRACE(11);
            asm volatile("fence.acq_rel.gpu;" ::: "memory");
            TRACE(12);
            asm volatile("red.relaxed.gpu.global.add.u32 [%0], 1;" :: "l"(scr->cnt + hkv * 32) : "memory");
            #pragma unroll 1
            for (uint32_t n = 0; (int32_t)(ld_acq(scr->cnt + hkv * 32) - target) < 0; n++) if (n > SPIN_LIMIT) __trap();
            TRACE(3);
        }
        __syncwarp();
        {
            const uint32_t* pq = scr->q + bb * 2048 + hkv * 256 + lane * 4;
            uint4 v0, v1;
            #pragma unroll 1
            for (uint32_t n = 0; ; n++) {
                v0 = ld_rlx4(pq); v1 = ld_rlx4(pq + 128);
                if (!__any_sync(0xffffffffu, has_poison(v0) || has_poison(v1))) break;
                if (n > SPIN_LIMIT) __trap();
            }
            const uint32_t a = sb + SM_Q + (lane >> 4) * 272 + (lane & 15) * 16;
            sts128(a, v0); sts128(a + 544, v1);
            __syncwarp();
            if (lane == 0) { mbar_arrive(bar_q); TRACE(23); }
        }
        #pragma unroll 1
        for (uint32_t n = 0; __any_sync(0xffffffffu, (int32_t)(ld_acq(scr->cnt + (lane & 7) * 32) - target) < 0); n++)
            if (n > SPIN_LIMIT) __trap();
        if (lane == 0) TRACE(20);
        mbar_wait0(bar_full + 12 * 8);
        {
            const uint32_t* p3 = lane < 16 ? scr->h + kg * 448 + 384 + lane * 4 : scr->st + (cta ^ 1) * 8 + (lane & 1) * 4;
            uint4 v[4];
            #pragma unroll 1
            for (uint32_t n = 0; ; n++) {
                #pragma unroll
                for (int i = 0; i < 3; i++) v[i] = ld_rlx4(scr->h + kg * 448 + i * 128 + lane * 4);
                v[3] = ld_rlx4(p3);
                if (!__any_sync(0xffffffffu, has_poison(v[0]) || has_poison(v[1]) || has_poison(v[2]) || has_poison(v[3]))) break;
                if (n > SPIN_LIMIT) __trap();
            }
            #pragma unroll
            for (int i = 0; i < 3; i++) sts128(sb + SM_H + i * 512 + lane * 16, v[i]);
            if (lane < 18) sts128(lane < 16 ? sb + SM_H + 1536 + lane * 16 : sb + SM_ST + (lane & 1) * 16, v[3]);
        }
        __syncwarp();
        if (lane == 0) { mbar_arrive(bar_st); TRACE(32); }
        return;
    }

    const uint4 xa = *reinterpret_cast<const uint4*>(x + warp * 512 + lane * 8);
    const uint4 xb = *reinterpret_cast<const uint4*>(x + warp * 512 + 256 + lane * 8);
    if (lane == 0) {
        #pragma unroll 1
        for (int j = 1 + warp; j < NBAR; j += 8) mbar_init(bar_full + j * 8, 1);
        mbar_fence_init();
    }
    bar_init_done();
    if (tid == 0) TRACE(13);
    {
        float xv[16];
        const uint32_t xw[8] = {xa.x, xa.y, xa.z, xa.w, xb.x, xb.y, xb.z, xb.w};
        #pragma unroll
        for (int i = 0; i < 8; i++) { xv[2 * i] = bf_lo(xw[i]); xv[2 * i + 1] = bf_hi(xw[i]); }
        float s = 0.f;
        #pragma unroll
        for (int i = 0; i < 16; i++) s += xv[i];
        #pragma unroll
        for (int o = 16; o; o >>= 1) s += __shfl_xor_sync(0xffffffffu, s, o);
        const float mean = s * (1.f / 512.f);
        if (tid == 0) TRACE(14);
        float q = 0.f;
        #pragma unroll
        for (int i = 0; i < 16; i++) { const float d = xv[i] - mean; q += d * d; }
        #pragma unroll
        for (int o = 16; o; o >>= 1) q += __shfl_xor_sync(0xffffffffu, q, o);
        const float mb = bf16r(mean);
        const float den = bf16r(sqrt_approx(bf16r(bf16r(q * (1.f / 512.f)) + 1e-5f)));
        uint32_t o[8];
        #pragma unroll
        for (int i = 0; i < 8; i++)
            o[i] = pack_bf16(__fdividef(bf16r(xv[2 * i] - mb), den), __fdividef(bf16r(xv[2 * i + 1] - mb), den));
        sts128(sb + SM_XN + warp * 1040 + lane * 16, make_uint4(o[0], o[1], o[2], o[3]));
        sts128(sb + SM_XN + warp * 1040 + 512 + lane * 16, make_uint4(o[4], o[5], o[6], o[7]));
    }
    if (tid == 0) TRACE(15);
    bar_ln_done();
    if (tid == 0) TRACE(0);

    {
        uint32_t xf[4][2];
        #pragma unroll
        for (int s = 0; s < 4; s++) {
            const uint32_t a = sb + SM_XN + g * 1040 + (warp * 64 + s * 16 + 2 * t) * 2;
            xf[s][0] = lds32(a); xf[s][1] = lds32(a + 16);
        }
        float acc[3][4] = {};
        const int mi = lane >> 3, rr = lane & 7;
        const int krow = (warp & 3) * 64 + (mi >> 1) * 8 + rr;
        mbar_wait0(bar_full + (1 + (warp >> 2)) * 8);
        if (tid == 0) TRACE(16);
        if (tid == 128) TRACE(17);
        #pragma unroll
        for (int s = 0; s < 4; s++) {
            const int r = krow + s * 16;
            #pragma unroll
            for (int mt = 0; mt < 2; mt++) {
                uint32_t a[4];
                ldsm_x4_t(a, sb + (1 + (warp >> 2)) * SLOT + r * 64 + (((2 * mt + (mi & 1)) ^ ((r >> 1) & 3)) << 4));
                mma16816(acc[mt], a[0], a[1], a[2], a[3], xf[s][0], xf[s][1]);
            }
        }
        if (cta < 112) {
            mbar_wait0(bar_full + 3 * 8);
            if (tid == 0) TRACE(18);
            #pragma unroll
            for (int s = 0; s < 4; s++) {
                const int r = (warp >> 2) * 256 + krow + s * 16;
                uint32_t a[4];
                ldsm_x4_t(a, sb + 3 * SLOT + r * 32 + (((mi & 1) ^ ((r >> 2) & 1)) << 4));
                mma16816(acc[2], a[0], a[1], a[2], a[3], xf[s][0], xf[s][1]);
            }
        }
        #pragma unroll
        for (int mt = 0; mt < 3; mt++)
            sts128(sb + SM_RED + (warp * 3 + mt) * 512 + lane * 16,
                   make_uint4(__float_as_uint(acc[mt][0]), __float_as_uint(acc[mt][1]), __float_as_uint(acc[mt][2]), __float_as_uint(acc[mt][3])));
    }
    bar_consumers();
    if (tid == 0) { TRACE(1); mbar_arrive(bar_emptyA); }
    if (tid < 192) {
        const int tile = tid < 128 ? ((tid >> 3) & 1) : 2;
        const int b = tid < 128 ? (tid >> 4) : ((tid - 128) >> 3);
        const int j = tid & 7;
        const uint32_t a = sb + SM_RED + tile * 512 + (4 * ((2 * j) & 7) + (b >> 1)) * 16 + (2 * (j >> 2) + (b & 1)) * 4;
        float v0 = 0.f, v1 = 0.f;
        #pragma unroll
        for (int w = 0; w < 8; w++) { v0 += lds32f(a + w * 1536); v1 += lds32f(a + w * 1536 + 64); }
        if (tid < 128) {
            st_rlx(scr->q + b * 2048 + cta * 16 + (tid & 15), unpoison(pack_bf16(v0, v1)));
        } else if (cta < 112) {
            v0 = bf16r(v0); v1 = bf16r(v1);
            v0 = __fdividef(v0, 1.f + __expf(-v0));
            v1 = __fdividef(v1, 1.f + __expf(-v1));
            st_rlx(scr->h + cta * 64 + b * 8 + 2 * (j & 3) + (j >> 2), unpoison(pack_bf16(v0, v1)));
        }
    }
    if (tid == 0) TRACE(2);

    float sc[4][4] = {};
    {
        uint4 qf[4];
        mbar_wait0(bar_q);
        #pragma unroll
        for (int j = 0; j < 4; j++) qf[j] = lds128(sb + SM_Q + (g & 3) * 272 + (4 * (j ^ (g >> 2)) + t) * 16);
        const int fill = warp == 0 ? 0 : warp + 3;
        mbar_wait0(bar_full + fill * 8);
        if (tid == 0 && qf[3].w != 0x12345) TRACE(19);
        const uint32_t kb = sb + fill * SLOT + g * 256 + t * 16;
        #pragma unroll
        for (int j = 0; j < 4; j++) {
            #pragma unroll
            for (int mt = 0; mt < 4; mt++) {
                const uint32_t a = kb + mt * 4096 + ((j ^ (g & 1)) << 6);
                const uint4 lo = lds128(a), hi = lds128(a + 2048);
                mma16816(sc[mt], lo.x, hi.x, lo.y, hi.y, qf[j].x, qf[j].y);
                mma16816(sc[mt], lo.z, hi.z, lo.w, hi.w, qf[j].z, qf[j].w);
            }
        }
        __syncwarp();
        if (lane == 0 && warp < 7) mbar_arrive(bar_emptyK + warp * 8);
    }
    if (tid == 0) TRACE(4);
    if (tid == 224) TRACE(5);
    const bool valid = (t >> 1) == (g & 1);
    const int h0 = 2 * (t & 1);
    {
        float m0 = -INFINITY, m1 = -INFINITY;
        #pragma unroll
        for (int mt = 0; mt < 4; mt++) {
            #pragma unroll
            for (int i = 0; i < 4; i++) sc[mt][i] = bf16r(bf16r(sc[mt][i]) * 0.08838834764831845f);
            m0 = fmaxf(m0, fmaxf(sc[mt][0], sc[mt][2]));
            m1 = fmaxf(m1, fmaxf(sc[mt][1], sc[mt][3]));
        }
        if (!valid) { m0 = -INFINITY; m1 = -INFINITY; }
        #pragma unroll
        for (int o = 2; o <= 16; o <<= 1) {
            m0 = fmaxf(m0, __shfl_xor_sync(0xffffffffu, m0, o));
            m1 = fmaxf(m1, __shfl_xor_sync(0xffffffffu, m1, o));
        }
        if (lane < 2) { sts32f(sb + SM_WMAX + warp * 16 + h0 * 4, m0); sts32f(sb + SM_WMAX + warp * 16 + h0 * 4 + 4, m1); }
    }
    bar_consumers();
    if (tid == 0) TRACE(21);
    float mloc0 = -INFINITY, mloc1 = -INFINITY;
    {
        #pragma unroll
        for (int w = 0; w < 8; w++) {
            mloc0 = fmaxf(mloc0, lds32f(sb + SM_WMAX + w * 16 + h0 * 4));
            mloc1 = fmaxf(mloc1, lds32f(sb + SM_WMAX + w * 16 + h0 * 4 + 4));
        }
        const float L2E = 1.4426950408889634f;
        float l0 = 0.f, l1 = 0.f;
        const uint32_t pa = sb + SM_P + (h0 * 260 + warp * 32 + (g & 3) * 8 + (g >> 2)) * 4;
        #pragma unroll
        for (int mt = 0; mt < 4; mt++) {
            const float p0 = ex2((sc[mt][0] - mloc0) * L2E), p2 = ex2((sc[mt][2] - mloc0) * L2E);
            const float p1 = ex2((sc[mt][1] - mloc1) * L2E), p3 = ex2((sc[mt][3] - mloc1) * L2E);
            l0 += p0 + p2; l1 += p1 + p3;
            if (valid) { sts32(pa + mt * 8, pack_bf16(p0, p2)); sts32(pa + 1040 + mt * 8, pack_bf16(p1, p3)); }
        }
        if (!valid) { l0 = 0.f; l1 = 0.f; }
        #pragma unroll
        for (int o = 2; o <= 16; o <<= 1) {
            l0 += __shfl_xor_sync(0xffffffffu, l0, o);
            l1 += __shfl_xor_sync(0xffffffffu, l1, o);
        }
        if (lane < 2) { sts32f(sb + SM_WSUM + warp * 16 + h0 * 4, l0); sts32f(sb + SM_WSUM + warp * 16 + h0 * 4 + 4, l1); }
    }
    if (tid == 0) TRACE(22);
    const int mtC = warp & 3, kh = warp >> 2;
    bar_consumers();
    if (tid == 0) TRACE(6);
    float lloc0 = 0.f, lloc1 = 0.f;
    #pragma unroll
    for (int w = 0; w < 8; w++) {
        lloc0 += lds32f(sb + SM_WSUM + w * 16 + h0 * 4);
        lloc1 += lds32f(sb + SM_WSUM + w * 16 + h0 * 4 + 4);
    }
    if (tid < 2) {
        st_rlx(scr->st + cta * 8 + h0, unpoison(__float_as_uint(mloc0)));
        st_rlx(scr->st + cta * 8 + h0 + 1, unpoison(__float_as_uint(mloc1)));
        st_rlx(scr->st + cta * 8 + 4 + h0, unpoison(__float_as_uint(lloc0)));
        st_rlx(scr->st + cta * 8 + 4 + h0 + 1, unpoison(__float_as_uint(lloc1)));
    }

    float oa[2][4] = {};
    float scale0 = 0.f, scale1 = 0.f;
    {
        const int mi = lane >> 3, rr = lane & 7;
        const int key = (rr >> 1) + 4 * (mi >> 1) + 8 * (rr & 1);
        const int rowp = 2 * key + (warp >> 2);
        const uint32_t voff = rowp * 128 + (((2 * (warp & 3) + (mi & 1)) ^ (rowp & 7)) << 4);
        #pragma unroll 1
        for (int vc = 0; vc < 8; vc++) {
            uint4 p0 = make_uint4(0u, 0u, 0u, 0u), p1 = p0;
            if (g < 4) {
                const uint32_t a = sb + SM_P + (g * 260 + vc * 32 + t * 8) * 4;
                p0 = lds128(a); p1 = lds128(a + 16);
            }
            if (vc == 7) {
                mbar_wait0(bar_st);
                const float L2E = 1.4426950408889634f;
                const float mo0 = lds32f(sb + SM_ST + h0 * 4), mo1 = lds32f(sb + SM_ST + h0 * 4 + 4);
                const float mg0 = fmaxf(mloc0, mo0), mg1 = fmaxf(mloc1, mo1);
                const float e0 = ex2((mloc0 - mg0) * L2E), e1 = ex2((mloc1 - mg1) * L2E);
                scale0 = __fdividef(e0, lloc0 * e0 + lds32f(sb + SM_ST + 16 + h0 * 4) * ex2((mo0 - mg0) * L2E));
                scale1 = __fdividef(e1, lloc1 * e1 + lds32f(sb + SM_ST + 20 + h0 * 4) * ex2((mo1 - mg1) * L2E));
            }
            const int fill = 11 + vc, slot = vc == 0 ? 11 : (vc < 4 ? vc : (vc == 4 ? 0 : vc - 1));
            mbar_wait0(bar_full + fill * 8);
            if (tid == 0) TRACE(24 + vc);
            const uint32_t vb = sb + slot * SLOT + voff;
            uint32_t a0[4], a1[4], a2[4], a3[4];
            ldsm_x4_t(a0, vb); ldsm_x4_t(a1, vb + 4096); ldsm_x4_t(a2, vb + 8192); ldsm_x4_t(a3, vb + 12288);
            mma16816(oa[0], a0[0], a0[1], a0[2], a0[3], p0.x, p0.y);
            mma16816(oa[1], a1[0], a1[1], a1[2], a1[3], p0.z, p0.w);
            mma16816(oa[0], a2[0], a2[1], a2[2], a2[3], p1.x, p1.y);
            mma16816(oa[1], a3[0], a3[1], a3[2], a3[3], p1.z, p1.w);
        }
        if (tid == 0) TRACE(7);
        const uint32_t lo = pack_bf16((oa[0][0] + oa[1][0]) * scale0, (oa[0][1] + oa[1][1]) * scale1);
        const uint32_t hi = pack_bf16((oa[0][2] + oa[1][2]) * scale0, (oa[0][3] + oa[1][3]) * scale1);
        const bool odd = g & 1;
        const uint32_t y = __shfl_xor_sync(0xffffffffu, odd ? lo : hi, 4);
        const uint32_t first = odd ? y : lo, second = odd ? hi : y;
        if (t < 2) {
            uint32_t* po = scr->o + cta * 256 + h0 * 64 + (warp >> 1) * 16 + (g >> 1) * 4 + (warp & 1) * 2 + (g & 1);
            st_rlx(po, unpoison(__byte_perm(first, second, 0x5410)));
            st_rlx(po + 64, unpoison(__byte_perm(first, second, 0x7632)));
        }
        if (tid == 0) TRACE(49);
    }

    {
        float acc[4][4] = {};
        const int mi = lane >> 3, rr = lane & 7;
        const int wrow = (mi >> 1) * 8 + rr;
        const uint32_t woff = wrow * 128 + (((2 * mtC + (mi & 1)) ^ rr) << 4);
        const int ocol = 64 * cg + 16 * mtC + g;
        const __nv_bfloat16* px = x + 2 * t * 512 + ocol;
        const __nv_bfloat16 x0 = px[0], x1 = px[512], x2 = px[8], x3 = px[520];
        mbar_wait0(bar_full + 19 * 8);
        if (tid == 0) TRACE(8);
        #pragma unroll
        for (int i = 0; i < 4; i++) {
            if (kh * 4 + i < 7) {
                uint32_t a[4];
                ldsm_x4_t(a, sb + 7 * SLOT + (kh * 4 + i) * 2048 + woff);
                const uint32_t ha = sb + SM_H + (kh * 4 + i) * 256 + lane * 8;
                mma16816(acc[i & 1], a[0], a[1], a[2], a[3], lds32(ha), lds32(ha + 4));
            }
        }
        mbar_wait0(bar_full + pace.opoll * 8);
        const uint32_t* po = scr->o + (hkv * 16 + warp * 2) * 256 + (kg & 1) * 128 + lane * 4;
        uint4 v0 = ld_rlx4(po), v1 = ld_rlx4(po + 256);
        if (tid == 0) TRACE(34);
        const uint32_t wb = sb + 8 * SLOT + kh * 4096 + woff;
        uint32_t a0[4], a1[4], a2[4], a3[4];
        mbar_wait0(bar_full + 20 * 8);
        ldsm_x4_t(a0, wb); ldsm_x4_t(a1, wb + 2048);
        mbar_wait0(bar_full + 21 * 8);
        ldsm_x4_t(a2, wb + 8192); ldsm_x4_t(a3, wb + 8192 + 2048);
        #pragma unroll 1
        for (uint32_t n = 0; ; n++) {
            const bool b0 = __any_sync(0xffffffffu, has_poison(v0)), b1 = __any_sync(0xffffffffu, has_poison(v1));
            if (!b0 && !b1) break;
            if (b0) v0 = ld_rlx4(po);
            if (b1) v1 = ld_rlx4(po + 256);
            if (n > SPIN_LIMIT) __trap();
        }
        sts128(sb + SM_O + warp * 1088 + lane * 16, v0);
        sts128(sb + SM_O + warp * 1088 + 544 + lane * 16, v1);
        bar_consumers();
        if (tid == 0) { TRACE(9); TRACE(48); }
        uint4 of[2][2][2];
        #pragma unroll
        for (int i = 0; i < 8; i++)
            of[i >> 2][(i >> 1) & 1][i & 1] = lds128(sb + SM_O + (2 * g + ((i >> 1) & 1)) * 544 + (i >> 2) * 256 + ((i & 1) * 2 + kh) * 64 + t * 16);
        #pragma unroll
        for (int hf = 0; hf < 2; hf++) {
            mma16816(acc[2 * hf], a0[0], a0[1], a0[2], a0[3], of[0][hf][0].x, of[0][hf][0].y);
            mma16816(acc[2 * hf + 1], a1[0], a1[1], a1[2], a1[3], of[0][hf][0].z, of[0][hf][0].w);
        }
        #pragma unroll
        for (int hf = 0; hf < 2; hf++) {
            mma16816(acc[2 * hf], a2[0], a2[1], a2[2], a2[3], of[0][hf][1].x, of[0][hf][1].y);
            mma16816(acc[2 * hf + 1], a3[0], a3[1], a3[2], a3[3], of[0][hf][1].z, of[0][hf][1].w);
        }
        #pragma unroll
        for (int pc = 0; pc < 2; pc++) {
            mbar_wait0(bar_full + (22 + pc) * 8);
            ldsm_x4_t(a0, wb + 16384 + pc * 8192); ldsm_x4_t(a1, wb + 16384 + pc * 8192 + 2048);
            #pragma unroll
            for (int hf = 0; hf < 2; hf++) {
                mma16816(acc[2 * hf], a0[0], a0[1], a0[2], a0[3], of[1][hf][pc].x, of[1][hf][pc].y);
                mma16816(acc[2 * hf + 1], a1[0], a1[1], a1[2], a1[3], of[1][hf][pc].z, of[1][hf][pc].w);
            }
        }
        float r[4];
        #pragma unroll
        for (int i = 0; i < 4; i++) r[i] = (acc[0][i] + acc[1][i]) + (acc[2][i] + acc[3][i]);
        if (tid == 0) TRACE(35);
        const uint32_t pa = sb + SM_PAIR + mtC * 512 + lane * 16;
        if (kh) {
            sts128(pa, make_uint4(__float_as_uint(r[0]), __float_as_uint(r[1]), __float_as_uint(r[2]), __float_as_uint(r[3])));
            asm volatile("bar.arrive %0, 64;" :: "r"(4 + mtC) : "memory");
            return;
        }
        asm volatile("bar.sync %0, 64;" :: "r"(4 + mtC) : "memory");
        const uint4 u = lds128(pa);
        r[0] += __uint_as_float(u.x); r[1] += __uint_as_float(u.y); r[2] += __uint_as_float(u.z); r[3] += __uint_as_float(u.w);
        float* pacc = scr->acc + (cg * 4 + mtC) * 256 + lane * 4;
        float4 o0, o1;
        asm volatile("atom.relaxed.gpu.global.add.v4.f32 {%0,%1,%2,%3}, [%4], {%5,%6,%7,%8};"
                     : "=f"(o0.x), "=f"(o0.y), "=f"(o0.z), "=f"(o0.w) : "l"(pacc), "f"(r[0]), "f"(r[1]), "f"(1.f), "f"(0.f) : "memory");
        asm volatile("atom.relaxed.gpu.global.add.v4.f32 {%0,%1,%2,%3}, [%4], {%5,%6,%7,%8};"
                     : "=f"(o1.x), "=f"(o1.y), "=f"(o1.z), "=f"(o1.w) : "l"(pacc + 128), "f"(r[2]), "f"(r[3]), "f"(1.f), "f"(0.f) : "memory");
        if (tid == 0) TRACE(10);
        __nv_bfloat16* pout = out + 2 * t * 512 + ocol;
        if (o0.z == 15.f) {
            pout[0] = __float2bfloat16_rn(__bfloat162float(x0) + (o0.x + r[0]));
            pout[512] = __float2bfloat16_rn(__bfloat162float(x1) + (o0.y + r[1]));
        }
        if (o1.z == 15.f) {
            pout[8] = __float2bfloat16_rn(__bfloat162float(x2) + (o1.x + r[2]));
            pout[520] = __float2bfloat16_rn(__bfloat162float(x3) + (o1.y + r[3]));
        }
    }
}

typedef CUresult (*EncodeTiledFn)(CUtensorMap*, CUtensorMapDataType, cuuint32_t, void*, const cuuint64_t*, const cuuint64_t*,
                                  const cuuint32_t*, const cuuint32_t*, CUtensorMapInterleave, CUtensorMapSwizzle,
                                  CUtensorMapL2promotion, CUtensorMapFloatOOBfill);

void make_map(EncodeTiledFn enc, CUtensorMap* m, const void* base, uint64_t cols, uint64_t rows, uint32_t box_cols,
              uint32_t box_rows, CUtensorMapSwizzle sw) {
    cuuint64_t gd[2] = {cols, rows};
    cuuint64_t gs[1] = {cols * 2};
    cuuint32_t bd[2] = {box_cols, box_rows};
    cuuint32_t es[2] = {1, 1};
    enc(m, CU_TENSOR_MAP_DATA_TYPE_BFLOAT16, 2, const_cast<void*>(base), gd, gs, bd, es, CU_TENSOR_MAP_INTERLEAVE_NONE, sw,
        CU_TENSOR_MAP_L2_PROMOTION_L2_256B, CU_TENSOR_MAP_FLOAT_OOB_FILL_NONE);
}

}

extern "C" void kernel_launch(void* const* d_in, const int* in_sizes, int n_in, void* d_out, int out_size) {
    (void)in_sizes; (void)n_in; (void)out_size;
    static EncodeTiledFn enc = nullptr;
    static Scratch* scr = nullptr;
    if (!enc) {
        cudaGetSymbolAddress((void**)&scr, g_scratch);
        void* fn = nullptr;
        cudaDriverEntryPointQueryResult qr;
        cudaGetDriverEntryPoint("cuTensorMapEncodeTiled", &fn, cudaEnableDefault, &qr);
        enc = (EncodeTiledFn)fn;
        cudaFuncSetAttribute(fused_decode_kernel, cudaFuncAttributeMaxDynamicSharedMemorySize, SMEM_BYTES);
    }
    TMaps tm;
    make_map(enc, &tm.wq, d_in[3], 4096, 512, 32, 256, CU_TENSOR_MAP_SWIZZLE_64B);
    make_map(enc, &tm.w1, d_in[6], 1792, 512, 16, 256, CU_TENSOR_MAP_SWIZZLE_32B);
    make_map(enc, &tm.v, d_in[2], 64, 8ull * 8 * 4096 * 2, 64, 128, CU_TENSOR_MAP_SWIZZLE_128B);
    make_map(enc, &tm.wo, d_in[4], 512, 4096, 64, 64, CU_TENSOR_MAP_SWIZZLE_128B);
    make_map(enc, &tm.w2, d_in[7], 512, 1792, 64, 112, CU_TENSOR_MAP_SWIZZLE_128B);
    fused_decode_kernel<<<NCTA, NTHREADS, SMEM_BYTES, cudaStreamPerThread>>>(
        (const __nv_bfloat16*)d_in[1], (const __nv_bfloat16*)d_in[0], (__nv_bfloat16*)d_out, scr, g_pace, tm);
}
```

```cpp
#include <cuda_runtime.h>
#include <cuda_bf16.h>
#include <cuda.h>
#include <stdint.h>

namespace {

constexpr int NCTA = 128;
constexpr int NTHREADS = 320;
constexpr int SLOT = 16384;
constexpr int NSLOT = 12;
constexpr int NFILL = 24;
constexpr uint32_t POISON = 0xFFFFFFFFu;
constexpr uint32_t SPIN_LIMIT = 1u << 22;

struct Pace { int t0, tau, tau_tail, first_tail, opoll; };
constexpr Pace g_pace = {100, 640, 640, 19, 20};

constexpr int SM_RING = 0;
constexpr int SM_XN = NSLOT * SLOT;
constexpr int SM_RED = SM_XN + 8 * 1040;
constexpr int SM_P = SM_RED + 8 * 3 * 512;
constexpr int SM_WMAX = SM_P + 4 * 260 * 4;
constexpr int SM_WSUM = SM_WMAX + 128;
constexpr int SM_ST = SM_WSUM + 128;
constexpr int SM_Q = SM_ST + 32;
constexpr int SM_H = SM_Q + 4 * 272;
constexpr int SM_O = SM_RED;
constexpr int SM_BAR = SM_H + 7 * 256;
constexpr int NBAR = NFILL + 7 + 3;
constexpr int SM_TOTAL = SM_BAR + NBAR * 8;
constexpr int SMEM_BYTES = SM_TOTAL + 1024;

struct TMaps { CUtensorMap wq, w1, v, wo, w2; };

struct Scratch {
    float acc[8 * 4 * 2 * 128];
    uint32_t o[NCTA * 256];
    uint32_t q[8 * 2048];
    uint32_t h[112 * 64];
    uint32_t st[NCTA * 8];
    uint32_t cnt[8 * 32];
};
__device__ __align__(128) Scratch g_scratch;

#define TRACE(i) do {} while (0)

__device__ __forceinline__ uint32_t clk32() { uint32_t c; asm volatile("mov.u32 %0, %clock;" : "=r"(c)); return c; }
__device__ __forceinline__ uint32_t gtime32() { uint32_t c; asm volatile("mov.u32 %0, %globaltimer_lo;" : "=r"(c)); return c; }
__device__ __forceinline__ uint32_t smem_u32(const void* p) { return (uint32_t)__cvta_generic_to_shared(p); }

__device__ __forceinline__ void mbar_init(uint32_t bar, uint32_t cnt) {
    asm volatile("mbarrier.init.shared::cta.b64 [%0], %1;" :: "r"(bar), "r"(cnt) : "memory");
}
__device__ __forceinline__ void mbar_fence_init() { asm volatile("fence.mbarrier_init.release.cluster;" ::: "memory"); }
__device__ __forceinline__ void mbar_expect_tx(uint32_t bar, uint32_t bytes) {
    asm volatile("mbarrier.arrive.expect_tx.shared::cta.b64 _, [%0], %1;" :: "r"(bar), "r"(bytes) : "memory");
}
__device__ __forceinline__ void mbar_arrive(uint32_t bar) {
    asm volatile("mbarrier.arrive.shared::cta.b64 _, [%0];" :: "r"(bar) : "memory");
}
__device__ __forceinline__ void mbar_wait0(uint32_t bar) {
    #pragma unroll 1
    for (uint32_t i = 0; i < SPIN_LIMIT; i++) {
        uint32_t ok;
        asm volatile("{\n.reg .pred p;\nmbarrier.try_wait.parity.shared::cta.b64 p, [%1], 0;\nselp.u32 %0, 1, 0, p;\n}"
                     : "=r"(ok) : "r"(bar) : "memory");
        if (ok) return;
    }
    __trap();
}
constexpr uint64_t EVICT_FIRST = 0x12F0000000000000ull;
__device__ __forceinline__ void bulk_g2s(uint32_t dst, const void* src, uint32_t bytes, uint32_t bar) {
    asm volatile("cp.async.bulk.shared::cluster.global.mbarrier::complete_tx::bytes.L2::cache_hint [%0], [%1], %2, [%3], %4;"
                 :: "r"(dst), "l"(src), "r"(bytes), "r"(bar), "l"(EVICT_FIRST) : "memory");
}
__device__ __forceinline__ void tma2d(uint32_t dst, const CUtensorMap* tm, int c0, int c1, uint32_t bar) {
    asm volatile("cp.async.bulk.tensor.2d.shared::cluster.global.mbarrier::complete_tx::bytes.L2::cache_hint [%0], [%1, {%3, %4}], [%2], %5;"
                 :: "r"(dst), "l"(tm), "r"(bar), "r"(c0), "r"(c1), "l"(EVICT_FIRST) : "memory");
}
__device__ __forceinline__ void bar_consumers() { asm volatile("bar.sync 1, 256;" ::: "memory"); }
__device__ __forceinline__ void bar_sync288(int id) { asm volatile("bar.sync %0, 288;" :: "r"(id) : "memory"); }
__device__ __forceinline__ void bar_arrive288(int id) { asm volatile("bar.arrive %0, 288;" :: "r"(id) : "memory"); }
template <typename T> __device__ __forceinline__ void keep64(T*& p) { asm volatile("" : "+l"(p)); }
__device__ __forceinline__ void keep32(uint32_t& v) { asm volatile("" : "+r"(v)); }
__device__ __forceinline__ void keepf(float& v) { asm volatile("" : "+f"(v)); }
__device__ __forceinline__ uint32_t hadd2_bf16(uint32_t a, uint32_t b) {
    uint32_t r; asm("add.rn.bf16x2 %0, %1, %2;" : "=r"(r) : "r"(a), "r"(b)); return r;
}
__device__ __forceinline__ void bar_ln_done() { asm volatile("bar.sync 3, 288;" ::: "memory"); }

__device__ __forceinline__ uint4 lds128(uint32_t a) {
    uint4 v; asm volatile("ld.shared.v4.u32 {%0,%1,%2,%3}, [%4];" : "=r"(v.x), "=r"(v.y), "=r"(v.z), "=r"(v.w) : "r"(a)); return v;
}
__device__ __forceinline__ uint32_t lds32(uint32_t a) { uint32_t v; asm volatile("ld.shared.u32 %0, [%1];" : "=r"(v) : "r"(a)); return v; }
__device__ __forceinline__ float lds32f(uint32_t a) { float v; asm volatile("ld.shared.f32 %0, [%1];" : "=f"(v) : "r"(a)); return v; }
__device__ __forceinline__ void sts32(uint32_t a, uint32_t v) { asm volatile("st.shared.u32 [%0], %1;" :: "r"(a), "r"(v) : "memory"); }
__device__ __forceinline__ void sts32f(uint32_t a, float v) { asm volatile("st.shared.f32 [%0], %1;" :: "r"(a), "f"(v) : "memory"); }
__device__ __forceinline__ void sts128(uint32_t a, uint4 v) {
    asm volatile("st.shared.v4.u32 [%0], {%1,%2,%3,%4};" :: "r"(a), "r"(v.x), "r"(v.y), "r"(v.z), "r"(v.w) : "memory");
}
__device__ __forceinline__ void ldsm_x4_t(uint32_t (&r)[4], uint32_t a) {
    asm volatile("ldmatrix.sync.aligned.m8n8.x4.trans.shared.b16 {%0,%1,%2,%3}, [%4];"
                 : "=r"(r[0]), "=r"(r[1]), "=r"(r[2]), "=r"(r[3]) : "r"(a));
}
__device__ __forceinline__ void mma16816(float (&c)[4], uint32_t a0, uint32_t a1, uint32_t a2, uint32_t a3, uint32_t b0, uint32_t b1) {
    asm volatile("mma.sync.aligned.m16n8k16.row.col.f32.bf16.bf16.f32 {%0,%1,%2,%3}, {%4,%5,%6,%7}, {%8,%9}, {%0,%1,%2,%3};"
                 : "+f"(c[0]), "+f"(c[1]), "+f"(c[2]), "+f"(c[3]) : "r"(a0), "r"(a1), "r"(a2), "r"(a3), "r"(b0), "r"(b1));
}

__device__ __forceinline__ uint32_t ld_rlx(const uint32_t* p) {
    uint32_t v; asm volatile("ld.relaxed.gpu.global.u32 %0, [%1];" : "=r"(v) : "l"(p) : "memory"); return v;
}
__device__ __forceinline__ uint32_t ld_acq(const uint32_t* p) {
    uint32_t v; asm volatile("ld.acquire.gpu.global.u32 %0, [%1];" : "=r"(v) : "l"(p) : "memory"); return v;
}
__device__ __forceinline__ uint2 ld_rlx2(const uint32_t* p) {
    uint2 v; asm volatile("ld.relaxed.gpu.global.v2.u32 {%0,%1}, [%2];" : "=r"(v.x), "=r"(v.y) : "l"(p) : "memory"); return v;
}
__device__ __forceinline__ uint4 ld_rlx4(const uint32_t* p) {
    uint4 v; asm volatile("ld.relaxed.gpu.global.v4.u32 {%0,%1,%2,%3}, [%4];" : "=r"(v.x), "=r"(v.y), "=r"(v.z), "=r"(v.w) : "l"(p) : "memory"); return v;
}
__device__ __forceinline__ void st_rlx(uint32_t* p, uint32_t v) {
    asm volatile("st.relaxed.gpu.global.u32 [%0], %1;" :: "l"(p), "r"(v) : "memory");
}
__device__ __forceinline__ void st_rlx4(uint32_t* p, uint4 v) {
    asm volatile("st.relaxed.gpu.global.v4.u32 [%0], {%1,%2,%3,%4};" :: "l"(p), "r"(v.x), "r"(v.y), "r"(v.z), "r"(v.w) : "memory");
}
__device__ __forceinline__ bool has_poison(const uint4& v) {
    return v.x == POISON || v.y == POISON || v.z == POISON || v.w == POISON;
}
__device__ __forceinline__ uint32_t unpoison(uint32_t w) { return w == POISON ? 0x7FFFFFFFu : w; }

__device__ __forceinline__ float sqrt_approx(float x) { float r; asm("sqrt.approx.f32 %0, %1;" : "=f"(r) : "f"(x)); return r; }
__device__ __forceinline__ float ex2(float x) { float r; asm("ex2.approx.f32 %0, %1;" : "=f"(r) : "f"(x)); return r; }
__device__ __forceinline__ float bf16r(float x) { return __bfloat162float(__float2bfloat16_rn(x)); }
__device__ __forceinline__ uint32_t pack_bf16(float lo, float hi) {
    uint32_t r; asm("cvt.rn.bf16x2.f32 %0, %1, %2;" : "=r"(r) : "f"(hi), "f"(lo)); return r;
}
__device__ __forceinline__ float bf_lo(uint32_t w) { return __uint_as_float(w << 16); }
__device__ __forceinline__ float bf_hi(uint32_t w) { return __uint_as_float(w & 0xFFFF0000u); }

__global__ void __launch_bounds__(NTHREADS, 1)
fused_decode_kernel(const __nv_bfloat16* __restrict__ kcache, const __nv_bfloat16* __restrict__ x,
                    __nv_bfloat16* __restrict__ out, Scratch* __restrict__ scr, const Pace pace,
                    const __grid_constant__ TMaps tm)
{
    extern __shared__ uint8_t smem_raw[];
    const uint32_t sb = (smem_u32(smem_raw) + 1023u) & ~1023u;
    const int tid = threadIdx.x, warp = tid >> 5, lane = tid & 31;
    const int cta = blockIdx.x;
    const int hkv = cta >> 4, bb = (cta >> 1) & 7, half = cta & 1;
    const int kg = cta >> 3, cg = cta & 7;
    const int g = lane >> 2, t = lane & 3;
    const uint32_t bar_full = sb + SM_BAR, bar_emptyK = bar_full + NFILL * 8, bar_emptyA = bar_emptyK + 7 * 8;
    const uint32_t bar_q = bar_emptyA + 8, bar_st = bar_q + 8;
    const int kvrow0 = (bb * 8 + hkv) * 4096 + 3072 + half * 512;

    uint32_t t_start = 0;
    if (tid == 256) {
        mbar_init(bar_full, 1);
        mbar_fence_init();
        mbar_expect_tx(bar_full, SLOT);
        bulk_g2s(sb, kcache + (size_t)kvrow0 * 128, SLOT, bar_full);
        t_start = gtime32();
        TRACE(43);
    }

    if (warp == 8) {
        if (lane == 0) {
            asm volatile("prefetch.tensormap [%0];" :: "l"(&tm.wq));
            asm volatile("prefetch.tensormap [%0];" :: "l"(&tm.w1));
            asm volatile("prefetch.tensormap [%0];" :: "l"(&tm.v));
            asm volatile("prefetch.tensormap [%0];" :: "l"(&tm.wo));
            asm volatile("prefetch.tensormap [%0];" :: "l"(&tm.w2));
            mbar_init(bar_full + 8, 1); mbar_init(bar_full + 16, 1); mbar_init(bar_full + 24, 1);
            mbar_fence_init();
        }
        __syncwarp();
        bar_arrive288(2);
        const uint32_t phase = (cta * pace.tau) >> 7;
        uint32_t due = pace.t0 + phase;
        #pragma unroll 1
        for (int i = 1; i < NFILL; i++) {
            if (i == 4) bar_sync288(4);
            if (lane == 0) {
                const int s = i < NSLOT ? i : (i < 15 ? i - 11 : (i == 15 ? 0 : (i < 20 ? i - NSLOT : 8 + ((i - 20) >> 1))));
                if (i >= NSLOT) mbar_wait0(i < 15 ? bar_emptyA : bar_emptyK + (s == 0 ? 0 : s - 3) * 8);
                #pragma unroll 1
                for (uint32_t n = 0; n < SPIN_LIMIT && gtime32() - t_start < due; n++) {}
                const uint32_t bar = bar_full + i * 8, dst = sb + s * SLOT;
                const int tau = i >= pace.first_tail ? pace.tau_tail : pace.tau;
                if (i <= 2) {
                    mbar_expect_tx(bar, SLOT);
                    tma2d(dst, &tm.wq, cta * 32, (i - 1) * 256, bar);
                } else if (i == 3) {
                    if (cta < 112) {
                        mbar_expect_tx(bar, SLOT);
                        tma2d(dst, &tm.w1, cta * 16, 0, bar);
                        tma2d(dst + 8192, &tm.w1, cta * 16, 256, bar);
                    }
                } else if (i <= 10) {
                    mbar_expect_tx(bar, SLOT);
                    bulk_g2s(dst, kcache + ((size_t)kvrow0 + (i - 3) * 64) * 128, SLOT, bar);
                } else if (i <= 18) {
                    mbar_expect_tx(bar, SLOT);
                    tma2d(dst, &tm.v, 0, (kvrow0 + (i - 11) * 64) * 2, bar);
                } else if (i == 19) {
                    mbar_expect_tx(bar, 112 * 128);
                    tma2d(dst, &tm.w2, cg * 64, kg * 112, bar);
                } else {
                    mbar_expect_tx(bar, SLOT / 2);
                    tma2d(dst + (i & 1) * 8192, &tm.wo, cg * 64, kg * 256 + (i - 20) * 64, bar);
                }
                due += (i == 3 || i == 19) ? (tau * 7) >> 3 : (i >= 20 ? tau >> 1 : tau);
                if (i == 19) due -= phase >> 1;
            }
            __syncwarp();
        }
        return;
    }

    if (warp == 9) {
        const uint32_t cnt0 = ld_rlx(scr->cnt + hkv * 32);
        const uint4 pz = make_uint4(POISON, POISON, POISON, POISON);
        st_rlx4(scr->q + (lane >> 2) * 2048 + cta * 16 + (lane & 3) * 4, pz);
        if (lane < 16 && cta < 112) st_rlx4(scr->h + cta * 64 + lane * 4, pz);
        if (lane < 2) st_rlx4(scr->st + cta * 8 + lane * 4, pz);
        st_rlx4(scr->o + cta * 256 + lane * 4, pz);
        st_rlx4(scr->o + cta * 256 + 128 + lane * 4, pz);
        if (lane < 16) st_rlx4(reinterpret_cast<uint32_t*>(scr->acc) + cta * 64 + lane * 4, make_uint4(0u, 0u, 0u, 0u));
        bar_ln_done();
        const uint32_t target = (cnt0 & ~15u) + 16u;
        if (lane == 0) {
            TRACE(11);
            asm volatile("fence.acq_rel.gpu;" ::: "memory");
            TRACE(12);
            asm volatile("red.relaxed.gpu.global.add.u32 [%0], 1;" :: "l"(scr->cnt + hkv * 32) : "memory");
            #pragma unroll 1
            for (uint32_t n = 0; (int32_t)(ld_acq(scr->cnt + hkv * 32) - target) < 0; n++) if (n > SPIN_LIMIT) __trap();
            TRACE(3);
        }
        __syncwarp();
        {
            const uint32_t* pq = scr->q + bb * 2048 + hkv * 256 + lane * 4;
            uint4 v0, v1;
            #pragma unroll 1
            for (uint32_t n = 0; ; n++) {
                v0 = ld_rlx4(pq); v1 = ld_rlx4(pq + 128);
                if (!__any_sync(0xffffffffu, has_poison(v0) || has_poison(v1))) break;
                if (n > SPIN_LIMIT) __trap();
            }
            const uint32_t a = sb + SM_Q + (lane >> 4) * 272 + (lane & 15) * 16;
            sts128(a, v0); sts128(a + 544, v1);
            __syncwarp();
            if (lane == 0) { mbar_arrive(bar_q); TRACE(23); }
        }
        #pragma unroll 1
        for (uint32_t n = 0; __any_sync(0xffffffffu, (int32_t)(ld_acq(scr->cnt + (lane & 7) * 32) - target) < 0); n++)
            if (n > SPIN_LIMIT) __trap();
        if (lane == 0) TRACE(20);
        mbar_wait0(bar_full + 12 * 8);
        {
            const uint32_t* p3 = lane < 16 ? scr->h + kg * 448 + 384 + lane * 4 : scr->st + (cta ^ 1) * 8 + (lane & 1) * 4;
            uint4 v[4];
            #pragma unroll 1
            for (uint32_t n = 0; ; n++) {
                #pragma unroll
                for (int i = 0; i < 3; i++) v[i] = ld_rlx4(scr->h + kg * 448 + i * 128 + lane * 4);
                v[3] = ld_rlx4(p3);
                if (!__any_sync(0xffffffffu, has_poison(v[0]) || has_poison(v[1]) || has_poison(v[2]) || has_poison(v[3]))) break;
                if (n > SPIN_LIMIT) __trap();
            }
            #pragma unroll
            for (int i = 0; i < 3; i++) sts128(sb + SM_H + i * 512 + lane * 16, v[i]);
            if (lane < 18) sts128(lane < 16 ? sb + SM_H + 1536 + lane * 16 : sb + SM_ST + (lane & 1) * 16, v[3]);
        }
        __syncwarp();
        if (lane == 0) { mbar_arrive(bar_st); TRACE(32); }
        return;
    }

    const uint4 xa = *reinterpret_cast<const uint4*>(x + warp * 512 + lane * 8);
    const uint4 xb = *reinterpret_cast<const uint4*>(x + warp * 512 + 256 + lane * 8);
    if (lane == 0) {
        #pragma unroll 1
        for (int j = 4 + warp; j < NBAR; j += 8) mbar_init(bar_full + j * 8, 1);
        mbar_fence_init();
    }
    __syncwarp();
    bar_arrive288(4);
    if (tid == 0) TRACE(13);
    {
        float xv[16];
        const uint32_t xw[8] = {xa.x, xa.y, xa.z, xa.w, xb.x, xb.y, xb.z, xb.w};
        #pragma unroll
        for (int i = 0; i < 8; i++) { xv[2 * i] = bf_lo(xw[i]); xv[2 * i + 1] = bf_hi(xw[i]); }
        float s = 0.f;
        #pragma unroll
        for (int i = 0; i < 16; i++) s += xv[i];
        #pragma unroll
        for (int o = 16; o; o >>= 1) s += __shfl_xor_sync(0xffffffffu, s, o);
        const float mean = s * (1.f / 512.f);
        if (tid == 0) TRACE(14);
        float q = 0.f;
        #pragma unroll
        for (int i = 0; i < 16; i++) { const float d = xv[i] - mean; q += d * d; }
        #pragma unroll
        for (int o = 16; o; o >>= 1) q += __shfl_xor_sync(0xffffffffu, q, o);
        const float mb = bf16r(mean);
        const float den = bf16r(sqrt_approx(bf16r(bf16r(q * (1.f / 512.f)) + 1e-5f)));
        uint32_t o[8];
        #pragma unroll
        for (int i = 0; i < 8; i++)
            o[i] = pack_bf16(__fdividef(bf16r(xv[2 * i] - mb), den), __fdividef(bf16r(xv[2 * i + 1] - mb), den));
        sts128(sb + SM_XN + warp * 1040 + lane * 16, make_uint4(o[0], o[1], o[2], o[3]));
        sts128(sb + SM_XN + warp * 1040 + 512 + lane * 16, make_uint4(o[4], o[5], o[6], o[7]));
    }
    if (tid == 0) TRACE(15);
    bar_sync288(2);
    bar_ln_done();
    if (tid == 0) TRACE(0);

    {
        uint32_t xf[4][2];
        #pragma unroll
        for (int s = 0; s < 4; s++) {
            const uint32_t a = sb + SM_XN + g * 1040 + (warp * 64 + s * 16 + 2 * t) * 2;
            xf[s][0] = lds32(a); xf[s][1] = lds32(a + 16);
        }
        float acc[3][4] = {};
        const int mi = lane >> 3, rr = lane & 7;
        const int krow = (warp & 3) * 64 + (mi >> 1) * 8 + rr;
        mbar_wait0(bar_full + (1 + (warp >> 2)) * 8);
        if (tid == 0) TRACE(16);
        if (tid == 128) TRACE(17);
        #pragma unroll
        for (int s = 0; s < 4; s++) {
            const int r = krow + s * 16;
            #pragma unroll
            for (int mt = 0; mt < 2; mt++) {
                uint32_t a[4];
                ldsm_x4_t(a, sb + (1 + (warp >> 2)) * SLOT + r * 64 + (((2 * mt + (mi & 1)) ^ ((r >> 1) & 3)) << 4));
                mma16816(acc[mt], a[0], a[1], a[2], a[3], xf[s][0], xf[s][1]);
            }
        }
        if (cta < 112) {
            mbar_wait0(bar_full + 3 * 8);
            if (tid == 0) TRACE(18);
            #pragma unroll
            for (int s = 0; s < 4; s++) {
                const int r = (warp >> 2) * 256 + krow + s * 16;
                uint32_t a[4];
                ldsm_x4_t(a, sb + 3 * SLOT + r * 32 + (((mi & 1) ^ ((r >> 2) & 1)) << 4));
                mma16816(acc[2], a[0], a[1], a[2], a[3], xf[s][0], xf[s][1]);
            }
        }
        #pragma unroll
        for (int mt = 0; mt < 3; mt++)
            sts128(sb + SM_RED + (warp * 3 + mt) * 512 + lane * 16,
                   make_uint4(__float_as_uint(acc[mt][0]), __float_as_uint(acc[mt][1]), __float_as_uint(acc[mt][2]), __float_as_uint(acc[mt][3])));
    }
    bar_consumers();
    if (tid == 0) { TRACE(1); mbar_arrive(bar_emptyA); }
    if (tid < 192) {
        const int tile = tid < 128 ? ((tid >> 3) & 1) : 2;
        const int b = tid < 128 ? (tid >> 4) : ((tid - 128) >> 3);
        const int j = tid & 7;
        const uint32_t a = sb + SM_RED + tile * 512 + (4 * ((2 * j) & 7) + (b >> 1)) * 16 + (2 * (j >> 2) + (b & 1)) * 4;
        float v0 = 0.f, v1 = 0.f;
        #pragma unroll
        for (int w = 0; w < 8; w++) { v0 += lds32f(a + w * 1536); v1 += lds32f(a + w * 1536 + 64); }
        if (tid < 128) {
            st_rlx(scr->q + b * 2048 + cta * 16 + (tid & 15), unpoison(pack_bf16(v0, v1)));
        } else if (cta < 112) {
            v0 = bf16r(v0); v1 = bf16r(v1);
            v0 = __fdividef(v0, 1.f + __expf(-v0));
            v1 = __fdividef(v1, 1.f + __expf(-v1));
            st_rlx(scr->h + cta * 64 + b * 8 + 2 * (j & 3) + (j >> 2), unpoison(pack_bf16(v0, v1)));
        }
    }
    if (tid == 0) TRACE(2);

    float sc[4][4] = {};
    {
        uint4 qf[4];
        mbar_wait0(bar_q);
        #pragma unroll
        for (int j = 0; j < 4; j++) qf[j] = lds128(sb + SM_Q + (g & 3) * 272 + (4 * (j ^ (g >> 2)) + t) * 16);
        const int fill = warp == 0 ? 0 : warp + 3;
        mbar_wait0(bar_full + fill * 8);
        if (tid == 0 && qf[3].w != 0x12345) TRACE(19);
        const uint32_t kb = sb + fill * SLOT + g * 256 + t * 16;
        #pragma unroll
        for (int j = 0; j < 4; j++) {
            #pragma unroll
            for (int mt = 0; mt < 4; mt++) {
                const uint32_t a = kb + mt * 4096 + ((j ^ (g & 1)) << 6);
                const uint4 lo = lds128(a), hi = lds128(a + 2048);
                mma16816(sc[mt], lo.x, hi.x, lo.y, hi.y, qf[j].x, qf[j].y);
                mma16816(sc[mt], lo.z, hi.z, lo.w, hi.w, qf[j].z, qf[j].w);
            }
        }
        __syncwarp();
        if (lane == 0 && warp < 7) mbar_arrive(bar_emptyK + warp * 8);
    }
    if (tid == 0) TRACE(4);
    if (tid == 224) TRACE(5);
    const bool valid = (t >> 1) == (g & 1);
    const int h0 = 2 * (t & 1);
    {
        float m0 = -INFINITY, m1 = -INFINITY;
        #pragma unroll
        for (int mt = 0; mt < 4; mt++) {
            #pragma unroll
            for (int i = 0; i < 4; i++) sc[mt][i] = bf16r(bf16r(sc[mt][i]) * 0.08838834764831845f);
            m0 = fmaxf(m0, fmaxf(sc[mt][0], sc[mt][2]));
            m1 = fmaxf(m1, fmaxf(sc[mt][1], sc[mt][3]));
        }
        if (!valid) { m0 = -INFINITY; m1 = -INFINITY; }
        #pragma unroll
        for (int o = 2; o <= 16; o <<= 1) {
            m0 = fmaxf(m0, __shfl_xor_sync(0xffffffffu, m0, o));
            m1 = fmaxf(m1, __shfl_xor_sync(0xffffffffu, m1, o));
        }
        if (lane < 2) { sts32f(sb + SM_WMAX + warp * 16 + h0 * 4, m0); sts32f(sb + SM_WMAX + warp * 16 + h0 * 4 + 4, m1); }
    }
    bar_consumers();
    if (tid == 0) TRACE(21);
    float mloc0 = -INFINITY, mloc1 = -INFINITY;
    {
        #pragma unroll
        for (int w = 0; w < 8; w++) {
            mloc0 = fmaxf(mloc0, lds32f(sb + SM_WMAX + w * 16 + h0 * 4));
            mloc1 = fmaxf(mloc1, lds32f(sb + SM_WMAX + w * 16 + h0 * 4 + 4));
        }
        const float L2E = 1.4426950408889634f;
        float l0 = 0.f, l1 = 0.f;
        const uint32_t pa = sb + SM_P + (h0 * 260 + warp * 32 + (g & 3) * 8 + (g >> 2)) * 4;
        #pragma unroll
        for (int mt = 0; mt < 4; mt++) {
            const float p0 = ex2((sc[mt][0] - mloc0) * L2E), p2 = ex2((sc[mt][2] - mloc0) * L2E);
            const float p1 = ex2((sc[mt][1] - mloc1) * L2E), p3 = ex2((sc[mt][3] - mloc1) * L2E);
            l0 += p0 + p2; l1 += p1 + p3;
            if (valid) { sts32(pa + mt * 8, pack_bf16(p0, p2)); sts32(pa + 1040 + mt * 8, pack_bf16(p1, p3)); }
        }
        if (!valid) { l0 = 0.f; l1 = 0.f; }
        #pragma unroll
        for (int o = 2; o <= 16; o <<= 1) {
            l0 += __shfl_xor_sync(0xffffffffu, l0, o);
            l1 += __shfl_xor_sync(0xffffffffu, l1, o);
        }
        if (lane < 2) { sts32f(sb + SM_WSUM + warp * 16 + h0 * 4, l0); sts32f(sb + SM_WSUM + warp * 16 + h0 * 4 + 4, l1); }
    }
    if (tid == 0) TRACE(22);
    bar_consumers();
    if (tid == 0) TRACE(6);
    float lloc0 = 0.f, lloc1 = 0.f;
    #pragma unroll
    for (int w = 0; w < 8; w++) {
        lloc0 += lds32f(sb + SM_WSUM + w * 16 + h0 * 4);
        lloc1 += lds32f(sb + SM_WSUM + w * 16 + h0 * 4 + 4);
    }
    if (tid < 2) {
        st_rlx(scr->st + cta * 8 + h0, unpoison(__float_as_uint(mloc0)));
        st_rlx(scr->st + cta * 8 + h0 + 1, unpoison(__float_as_uint(mloc1)));
        st_rlx(scr->st + cta * 8 + 4 + h0, unpoison(__float_as_uint(lloc0)));
        st_rlx(scr->st + cta * 8 + 4 + h0 + 1, unpoison(__float_as_uint(lloc1)));
    }

    float oa[2][4] = {};
    float scale0 = 0.f, scale1 = 0.f;
    {
        const int mi = lane >> 3, rr = lane & 7;
        const int key = (rr >> 1) + 4 * (mi >> 1) + 8 * (rr & 1);
        const int rowp = 2 * key + (warp >> 2);
        const uint32_t voff = rowp * 128 + (((2 * (warp & 3) + (mi & 1)) ^ (rowp & 7)) << 4);
        #pragma unroll 1
        for (int vc = 0; vc < 8; vc++) {
            uint4 p0 = make_uint4(0u, 0u, 0u, 0u), p1 = p0;
            if (g < 4) {
                const uint32_t a = sb + SM_P + (g * 260 + vc * 32 + t * 8) * 4;
                p0 = lds128(a); p1 = lds128(a + 16);
            }
            if (vc == 7) {
                mbar_wait0(bar_st);
                const float L2E = 1.4426950408889634f;
                const float mo0 = lds32f(sb + SM_ST + h0 * 4), mo1 = lds32f(sb + SM_ST + h0 * 4 + 4);
                const float mg0 = fmaxf(mloc0, mo0), mg1 = fmaxf(mloc1, mo1);
                const float e0 = ex2((mloc0 - mg0) * L2E), e1 = ex2((mloc1 - mg1) * L2E);
                scale0 = __fdividef(e0, lloc0 * e0 + lds32f(sb + SM_ST + 16 + h0 * 4) * ex2((mo0 - mg0) * L2E));
                scale1 = __fdividef(e1, lloc1 * e1 + lds32f(sb + SM_ST + 20 + h0 * 4) * ex2((mo1 - mg1) * L2E));
            }
            const int fill = 11 + vc, slot = vc == 0 ? 11 : (vc < 4 ? vc : (vc == 4 ? 0 : vc - 1));
            mbar_wait0(bar_full + fill * 8);
            if (tid == 0) TRACE(24 + vc);
            const uint32_t vb = sb + slot * SLOT + voff;
            uint32_t a0[4], a1[4], a2[4], a3[4];
            ldsm_x4_t(a0, vb); ldsm_x4_t(a1, vb + 4096); ldsm_x4_t(a2, vb + 8192); ldsm_x4_t(a3, vb + 12288);
            mma16816(oa[0], a0[0], a0[1], a0[2], a0[3], p0.x, p0.y);
            mma16816(oa[1], a1[0], a1[1], a1[2], a1[3], p0.z, p0.w);
            mma16816(oa[0], a2[0], a2[1], a2[2], a2[3], p1.x, p1.y);
            mma16816(oa[1], a3[0], a3[1], a3[2], a3[3], p1.z, p1.w);
        }
        if (tid == 0) TRACE(7);
        const uint32_t lo = pack_bf16((oa[0][0] + oa[1][0]) * scale0, (oa[0][1] + oa[1][1]) * scale1);
        const uint32_t hi = pack_bf16((oa[0][2] + oa[1][2]) * scale0, (oa[0][3] + oa[1][3]) * scale1);
        const bool odd = g & 1;
        const uint32_t y = __shfl_xor_sync(0xffffffffu, odd ? lo : hi, 4);
        const uint32_t first = odd ? y : lo, second = odd ? hi : y;
        if (t < 2) {
            uint32_t* po = scr->o + cta * 256 + h0 * 64 + (warp >> 1) * 16 + (g >> 1) * 4 + (warp & 1) * 2 + (g & 1);
            st_rlx(po, unpoison(__byte_perm(first, second, 0x5410)));
            st_rlx(po + 64, unpoison(__byte_perm(first, second, 0x7632)));
        }
        if (tid == 0) TRACE(49);
    }

    {
        const uint32_t* po = scr->o + (hkv * 16 + warp * 2) * 256 + (kg & 1) * 128 + lane * 4;
        keep64(po);
        float acc[4][4] = {};
        uint32_t wa[3][4][4];
        const int mi = lane >> 3, rr = lane & 7;
        uint32_t wb = sb + 8 * SLOT + ((mi >> 1) * 8 + rr) * 128 + (((2 * warp + (mi & 1)) ^ rr) << 4);
        const int ocol = 64 * cg + 16 * warp + g;
        float* pacc = scr->acc + (cg * 4 + warp) * 256 + lane * 4;
        __nv_bfloat16* pout = out + 2 * t * 512 + ocol;
        float x0 = 0.f, x1 = 0.f, x2 = 0.f, x3 = 0.f;
        keep32(wb); keep64(pacc); keep64(pout);
        if (warp < 4) {
            const __nv_bfloat16* px = x + 2 * t * 512 + ocol;
            const __nv_bfloat16 b0 = px[0], b1 = px[512], b2 = px[8], b3 = px[520];
            mbar_wait0(bar_full + 19 * 8);
            if (tid == 0) TRACE(8);
            #pragma unroll
            for (int i = 0; i < 7; i++) {
                uint32_t a[4];
                ldsm_x4_t(a, wb - SLOT + i * 2048);
                const uint32_t ha = sb + SM_H + i * 256 + lane * 8;
                mma16816(acc[i & 3], a[0], a[1], a[2], a[3], lds32(ha), lds32(ha + 4));
            }
            x0 = __bfloat162float(b0); x1 = __bfloat162float(b1); x2 = __bfloat162float(b2); x3 = __bfloat162float(b3);
            keepf(x0); keepf(x1); keepf(x2); keepf(x3);
        }
        mbar_wait0(bar_full + pace.opoll * 8);
        uint4 v0 = ld_rlx4(po), v1 = ld_rlx4(po + 256);
        if (tid == 0) TRACE(34);
        if (warp < 4) {
            #pragma unroll
            for (int pc = 0; pc < 3; pc++) {
                mbar_wait0(bar_full + (20 + pc) * 8);
                #pragma unroll
                for (int k = 0; k < 4; k++) ldsm_x4_t(wa[pc][k], wb + pc * 8192 + k * 2048);
            }
        }
        #pragma unroll 1
        for (uint32_t n = 0; ; n++) {
            const bool b0 = __any_sync(0xffffffffu, has_poison(v0)), b1 = __any_sync(0xffffffffu, has_poison(v1));
            if (!b0 && !b1) break;
            if (b0) v0 = ld_rlx4(po);
            if (b1) v1 = ld_rlx4(po + 256);
            if (n > SPIN_LIMIT) __trap();
        }
        sts128(sb + SM_O + warp * 576 + lane * 16,
               make_uint4(hadd2_bf16(v0.x, v1.x), hadd2_bf16(v0.y, v1.y), hadd2_bf16(v0.z, v1.z), hadd2_bf16(v0.w, v1.w)));
        if (warp >= 4) { asm volatile("bar.arrive 1, 256;" ::: "memory"); return; }
        bar_consumers();
        if (tid == 0) { TRACE(9); TRACE(48); }
        uint4 of[8];
        #pragma unroll
        for (int i = 0; i < 8; i++) of[i] = lds128(sb + SM_O + g * 576 + i * 64 + t * 16);
        #pragma unroll
        for (int pc = 0; pc < 3; pc++) {
            mma16816(acc[0], wa[pc][0][0], wa[pc][0][1], wa[pc][0][2], wa[pc][0][3], of[2 * pc].x, of[2 * pc].y);
            mma16816(acc[1], wa[pc][1][0], wa[pc][1][1], wa[pc][1][2], wa[pc][1][3], of[2 * pc].z, of[2 * pc].w);
            mma16816(acc[2], wa[pc][2][0], wa[pc][2][1], wa[pc][2][2], wa[pc][2][3], of[2 * pc + 1].x, of[2 * pc + 1].y);
            mma16816(acc[3], wa[pc][3][0], wa[pc][3][1], wa[pc][3][2], wa[pc][3][3], of[2 * pc + 1].z, of[2 * pc + 1].w);
        }
        {
            uint32_t a0[4], a1[4], a2[4], a3[4];
            mbar_wait0(bar_full + 23 * 8);
            ldsm_x4_t(a0, wb + 24576); ldsm_x4_t(a1, wb + 24576 + 2048); ldsm_x4_t(a2, wb + 24576 + 4096); ldsm_x4_t(a3, wb + 24576 + 6144);
            mma16816(acc[0], a0[0], a0[1], a0[2], a0[3], of[6].x, of[6].y);
            mma16816(acc[1], a1[0], a1[1], a1[2], a1[3], of[6].z, of[6].w);
            mma16816(acc[2], a2[0], a2[1], a2[2], a2[3], of[7].x, of[7].y);
            mma16816(acc[3], a3[0], a3[1], a3[2], a3[3], of[7].z, of[7].w);
        }
        float r[4];
        #pragma unroll
        for (int i = 0; i < 4; i++) r[i] = (acc[0][i] + acc[1][i]) + (acc[2][i] + acc[3][i]);
        float4 o0, o1;
        asm volatile("atom.relaxed.gpu.global.add.v4.f32 {%0,%1,%2,%3}, [%4], {%5,%6,%7,%8};"
                     : "=f"(o0.x), "=f"(o0.y), "=f"(o0.z), "=f"(o0.w) : "l"(pacc), "f"(r[0]), "f"(r[1]), "f"(1.f), "f"(0.f) : "memory");
        asm volatile("atom.relaxed.gpu.global.add.v4.f32 {%0,%1,%2,%3}, [%4], {%5,%6,%7,%8};"
                     : "=f"(o1.x), "=f"(o1.y), "=f"(o1.z), "=f"(o1.w) : "l"(pacc + 128), "f"(r[2]), "f"(r[3]), "f"(1.f), "f"(0.f) : "memory");
        if (tid == 0) TRACE(10);
        r[0] += x0; r[1] += x1; r[2] += x2; r[3] += x3;
        if (o0.z == 15.f) {
            pout[0] = __float2bfloat16_rn(o0.x + r[0]);
            pout[512] = __float2bfloat16_rn(o0.y + r[1]);
        }
        if (o1.z == 15.f) {
            pout[8] = __float2bfloat16_rn(o1.x + r[2]);
            pout[520] = __float2bfloat16_rn(o1.y + r[3]);
        }
    }
}

typedef CUresult (*EncodeTiledFn)(CUtensorMap*, CUtensorMapDataType, cuuint32_t, void*, const cuuint64_t*, const cuuint64_t*,
                                  const cuuint32_t*, const cuuint32_t*, CUtensorMapInterleave, CUtensorMapSwizzle,
                                  CUtensorMapL2promotion, CUtensorMapFloatOOBfill);

void make_map(EncodeTiledFn enc, CUtensorMap* m, const void* base, uint64_t cols, uint64_t rows, uint32_t box_cols,
              uint32_t box_rows, CUtensorMapSwizzle sw) {
    cuuint64_t gd[2] = {cols, rows};
    cuuint64_t gs[1] = {cols * 2};
    cuuint32_t bd[2] = {box_cols, box_rows};
    cuuint32_t es[2] = {1, 1};
    enc(m, CU_TENSOR_MAP_DATA_TYPE_BFLOAT16, 2, const_cast<void*>(base), gd, gs, bd, es, CU_TENSOR_MAP_INTERLEAVE_NONE, sw,
        CU_TENSOR_MAP_L2_PROMOTION_L2_256B, CU_TENSOR_MAP_FLOAT_OOB_FILL_NONE);
}

}

extern "C" void kernel_launch(void* const* d_in, const int* in_sizes, int n_in, void* d_out, int out_size) {
    (void)in_sizes; (void)n_in; (void)out_size;
    static EncodeTiledFn enc = nullptr;
    static Scratch* scr = nullptr;
    if (!enc) {
        cudaGetSymbolAddress((void**)&scr, g_scratch);
        void* fn = nullptr;
        cudaDriverEntryPointQueryResult qr;
        cudaGetDriverEntryPoint("cuTensorMapEncodeTiled", &fn, cudaEnableDefault, &qr);
        enc = (EncodeTiledFn)fn;
        cudaFuncSetAttribute(fused_decode_kernel, cudaFuncAttributeMaxDynamicSharedMemorySize, SMEM_BYTES);
    }
    TMaps tm;
    make_map(enc, &tm.wq, d_in[3], 4096, 512, 32, 256, CU_TENSOR_MAP_SWIZZLE_64B);
    make_map(enc, &tm.w1, d_in[6], 1792, 512, 16, 256, CU_TENSOR_MAP_SWIZZLE_32B);
    make_map(enc, &tm.v, d_in[2], 64, 8ull * 8 * 4096 * 2, 64, 128, CU_TENSOR_MAP_SWIZZLE_128B);
    make_map(enc, &tm.wo, d_in[4], 512, 4096, 64, 64, CU_TENSOR_MAP_SWIZZLE_128B);
    make_map(enc, &tm.w2, d_in[7], 512, 1792, 64, 112, CU_TENSOR_MAP_SWIZZLE_128B);
    fused_decode_kernel<<<NCTA, NTHREADS, SMEM_BYTES, cudaStreamPerThread>>>(
        (const __nv_bfloat16*)d_in[1], (const __nv_bfloat16*)d_in[0], (__nv_bfloat16*)d_out, scr, g_pace, tm);
}
```

```cpp
#include <cuda_runtime.h>
#include <cuda_bf16.h>
#include <cuda.h>
#include <stdint.h>

namespace {

constexpr int NCTA = 128;
constexpr int NTHREADS = 320;
constexpr int SLOT = 16384;
constexpr int NSLOT = 12;
constexpr int NFILL = 24;
constexpr uint32_t POISON = 0xFFFFFFFFu;
constexpr uint32_t SPIN_LIMIT = 1u << 22;

struct Pace { int t0, tau, tail_extra, first_tail, opoll, scramble, qdelay; };
constexpr Pace g_pace = {700, 640, 50, 16, 20, 0, 300};

constexpr int SM_RING = 0;
constexpr int SM_XN = NSLOT * SLOT;
constexpr int SM_RED = SM_XN + 8 * 1040;
constexpr int SM_P = SM_RED + 8 * 3 * 512;
constexpr int SM_WMAX = SM_P + 4 * 260 * 4;
constexpr int SM_WSUM = SM_WMAX + 128;
constexpr int SM_ST = SM_WSUM + 128;
constexpr int SM_Q = SM_ST + 32;
constexpr int SM_H = SM_Q + 4 * 272;
constexpr int SM_O = SM_RED;
constexpr int SM_BAR = SM_H + 7 * 256;
constexpr int NBAR = NFILL + 7 + 3;
constexpr int SM_TOTAL = SM_BAR + NBAR * 8;
constexpr int SMEM_BYTES = SM_TOTAL + 1024;

struct TMaps { CUtensorMap wq, w1, v, wo, w2; };

struct Scratch {
    float acc[8 * 4 * 2 * 128];
    uint32_t o[NCTA * 256];
    uint32_t q[8 * 2048];
    uint32_t h[112 * 64];
    uint32_t st[NCTA * 8];
    uint32_t cnt[8 * 32];
};
__device__ __align__(128) Scratch g_scratch;

#define TRACE(i) do {} while (0)

__device__ __forceinline__ uint32_t clk32() { uint32_t c; asm volatile("mov.u32 %0, %clock;" : "=r"(c)); return c; }
__device__ __forceinline__ uint32_t gtime32() { uint32_t c; asm volatile("mov.u32 %0, %globaltimer_lo;" : "=r"(c)); return c; }
__device__ __forceinline__ uint32_t smem_u32(const void* p) { return (uint32_t)__cvta_generic_to_shared(p); }

__device__ __forceinline__ void mbar_init(uint32_t bar, uint32_t cnt) {
    asm volatile("mbarrier.init.shared::cta.b64 [%0], %1;" :: "r"(bar), "r"(cnt) : "memory");
}
__device__ __forceinline__ void mbar_fence_init() { asm volatile("fence.mbarrier_init.release.cluster;" ::: "memory"); }
__device__ __forceinline__ void mbar_expect_tx(uint32_t bar, uint32_t bytes) {
    asm volatile("mbarrier.arrive.expect_tx.shared::cta.b64 _, [%0], %1;" :: "r"(bar), "r"(bytes) : "memory");
}
__device__ __forceinline__ void mbar_arrive(uint32_t bar) {
    asm volatile("mbarrier.arrive.shared::cta.b64 _, [%0];" :: "r"(bar) : "memory");
}
__device__ __forceinline__ void mbar_wait0(uint32_t bar) {
    #pragma unroll 1
    for (uint32_t i = 0; i < SPIN_LIMIT; i++) {
        uint32_t ok;
        asm volatile("{\n.reg .pred p;\nmbarrier.try_wait.parity.shared::cta.b64 p, [%1], 0;\nselp.u32 %0, 1, 0, p;\n}"
                     : "=r"(ok) : "r"(bar) : "memory");
        if (ok) return;
    }
    __trap();
}
constexpr uint64_t EVICT_FIRST = 0x12F0000000000000ull;
__device__ __forceinline__ void bulk_g2s(uint32_t dst, const void* src, uint32_t bytes, uint32_t bar) {
    asm volatile("cp.async.bulk.shared::cluster.global.mbarrier::complete_tx::bytes.L2::cache_hint [%0], [%1], %2, [%3], %4;"
                 :: "r"(dst), "l"(src), "r"(bytes), "r"(bar), "l"(EVICT_FIRST) : "memory");
}
__device__ __forceinline__ void tma2d(uint32_t dst, const CUtensorMap* tm, int c0, int c1, uint32_t bar) {
    asm volatile("cp.async.bulk.tensor.2d.shared::cluster.global.mbarrier::complete_tx::bytes.L2::cache_hint [%0], [%1, {%3, %4}], [%2], %5;"
                 :: "r"(dst), "l"(tm), "r"(bar), "r"(c0), "r"(c1), "l"(EVICT_FIRST) : "memory");
}
__device__ __forceinline__ void bar_consumers() { asm volatile("bar.sync 1, 256;" ::: "memory"); }
__device__ __forceinline__ void bar_sync288(int id) { asm volatile("bar.sync %0, 288;" :: "r"(id) : "memory"); }
__device__ __forceinline__ void bar_arrive288(int id) { asm volatile("bar.arrive %0, 288;" :: "r"(id) : "memory"); }
template <typename T> __device__ __forceinline__ void keep64(T*& p) { asm volatile("" : "+l"(p)); }
__device__ __forceinline__ void keep32(uint32_t& v) { asm volatile("" : "+r"(v)); }
__device__ __forceinline__ void keepf(float& v) { asm volatile("" : "+f"(v)); }
__device__ __forceinline__ uint32_t hadd2_bf16(uint32_t a, uint32_t b) {
    uint32_t r; asm("add.rn.bf16x2 %0, %1, %2;" : "=r"(r) : "r"(a), "r"(b)); return r;
}
__device__ __forceinline__ void bar_ln_done() { asm volatile("bar.sync 3, 288;" ::: "memory"); }

__device__ __forceinline__ uint4 lds128(uint32_t a) {
    uint4 v; asm volatile("ld.shared.v4.u32 {%0,%1,%2,%3}, [%4];" : "=r"(v.x), "=r"(v.y), "=r"(v.z), "=r"(v.w) : "r"(a)); return v;
}
__device__ __forceinline__ uint32_t lds32(uint32_t a) { uint32_t v; asm volatile("ld.shared.u32 %0, [%1];" : "=r"(v) : "r"(a)); return v; }
__device__ __forceinline__ float lds32f(uint32_t a) { float v; asm volatile("ld.shared.f32 %0, [%1];" : "=f"(v) : "r"(a)); return v; }
__device__ __forceinline__ void sts32(uint32_t a, uint32_t v) { asm volatile("st.shared.u32 [%0], %1;" :: "r"(a), "r"(v) : "memory"); }
__device__ __forceinline__ void sts32f(uint32_t a, float v) { asm volatile("st.shared.f32 [%0], %1;" :: "r"(a), "f"(v) : "memory"); }
__device__ __forceinline__ void sts128(uint32_t a, uint4 v) {
    asm volatile("st.shared.v4.u32 [%0], {%1,%2,%3,%4};" :: "r"(a), "r"(v.x), "r"(v.y), "r"(v.z), "r"(v.w) : "memory");
}
__device__ __forceinline__ void ldsm_x4_t(uint32_t (&r)[4], uint32_t a) {
    asm volatile("ldmatrix.sync.aligned.m8n8.x4.trans.shared.b16 {%0,%1,%2,%3}, [%4];"
                 : "=r"(r[0]), "=r"(r[1]), "=r"(r[2]), "=r"(r[3]) : "r"(a));
}
__device__ __forceinline__ void mma16816(float (&c)[4], uint32_t a0, uint32_t a1, uint32_t a2, uint32_t a3, uint32_t b0, uint32_t b1) {
    asm volatile("mma.sync.aligned.m16n8k16.row.col.f32.bf16.bf16.f32 {%0,%1,%2,%3}, {%4,%5,%6,%7}, {%8,%9}, {%0,%1,%2,%3};"
                 : "+f"(c[0]), "+f"(c[1]), "+f"(c[2]), "+f"(c[3]) : "r"(a0), "r"(a1), "r"(a2), "r"(a3), "r"(b0), "r"(b1));
}

__device__ __forceinline__ uint32_t ld_rlx(const uint32_t* p) {
    uint32_t v; asm volatile("ld.relaxed.gpu.global.u32 %0, [%1];" : "=r"(v) : "l"(p) : "memory"); return v;
}
__device__ __forceinline__ uint32_t ld_acq(const uint32_t* p) {
    uint32_t v; asm volatile("ld.acquire.gpu.global.u32 %0, [%1];" : "=r"(v) : "l"(p) : "memory"); return v;
}
__device__ __forceinline__ uint2 ld_rlx2(const uint32_t* p) {
    uint2 v; asm volatile("ld.relaxed.gpu.global.v2.u32 {%0,%1}, [%2];" : "=r"(v.x), "=r"(v.y) : "l"(p) : "memory"); return v;
}
__device__ __forceinline__ uint4 ld_rlx4(const uint32_t* p) {
    uint4 v; asm volatile("ld.relaxed.gpu.global.v4.u32 {%0,%1,%2,%3}, [%4];" : "=r"(v.x), "=r"(v.y), "=r"(v.z), "=r"(v.w) : "l"(p) : "memory"); return v;
}
__device__ __forceinline__ void st_rlx(uint32_t* p, uint32_t v) {
    asm volatile("st.relaxed.gpu.global.u32 [%0], %1;" :: "l"(p), "r"(v) : "memory");
}
__device__ __forceinline__ void st_rlx4(uint32_t* p, uint4 v) {
    asm volatile("st.relaxed.gpu.global.v4.u32 [%0], {%1,%2,%3,%4};" :: "l"(p), "r"(v.x), "r"(v.y), "r"(v.z), "r"(v.w) : "memory");
}
__device__ __forceinline__ bool has_poison(const uint4& v) {
    return v.x == POISON || v.y == POISON || v.z == POISON || v.w == POISON;
}
__device__ __forceinline__ uint32_t unpoison(uint32_t w) { return w == POISON ? 0x7FFFFFFFu : w; }

__device__ __forceinline__ float sqrt_approx(float x) { float r; asm("sqrt.approx.f32 %0, %1;" : "=f"(r) : "f"(x)); return r; }
__device__ __forceinline__ float ex2(float x) { float r; asm("ex2.approx.f32 %0, %1;" : "=f"(r) : "f"(x)); return r; }
__device__ __forceinline__ float bf16r(float x) { return __bfloat162float(__float2bfloat16_rn(x)); }
__device__ __forceinline__ uint32_t pack_bf16(float lo, float hi) {
    uint32_t r; asm("cvt.rn.bf16x2.f32 %0, %1, %2;" : "=r"(r) : "f"(hi), "f"(lo)); return r;
}
__device__ __forceinline__ float bf_lo(uint32_t w) { return __uint_as_float(w << 16); }
__device__ __forceinline__ float bf_hi(uint32_t w) { return __uint_as_float(w & 0xFFFF0000u); }

__global__ void __launch_bounds__(NTHREADS, 1)
fused_decode_kernel(const __nv_bfloat16* __restrict__ kcache, const __nv_bfloat16* __restrict__ x,
                    __nv_bfloat16* __restrict__ out, Scratch* __restrict__ scr, const Pace pace,
                    const __grid_constant__ TMaps tm)
{
    extern __shared__ uint8_t smem_raw[];
    const uint32_t sb = (smem_u32(smem_raw) + 1023u) & ~1023u;
    const int tid = threadIdx.x, warp = tid >> 5, lane = tid & 31;
    const int cta = blockIdx.x;
    const int hkv = cta >> 4, bb = (cta >> 1) & 7, half = cta & 1;
    const int kg = cta >> 3, cg = cta & 7;
    const int g = lane >> 2, t = lane & 3;
    const uint32_t bar_full = sb + SM_BAR, bar_emptyK = bar_full + NFILL * 8, bar_emptyA = bar_emptyK + 7 * 8;
    const uint32_t bar_q = bar_emptyA + 8, bar_st = bar_q + 8;
    const int kvrow0 = (bb * 8 + hkv) * 4096 + 3072 + half * 512;

    uint32_t t_start = 0;
    if (tid == 256) {
        mbar_init(bar_full, 1);
        mbar_init(bar_full + 8, 1);
        mbar_fence_init();
        mbar_expect_tx(bar_full, SLOT);
        bulk_g2s(sb, kcache + (size_t)kvrow0 * 128, SLOT, bar_full);
        mbar_expect_tx(bar_full + 8, SLOT);
        bulk_g2s(sb + SLOT, kcache + (size_t)kvrow0 * 128 + 8192, SLOT, bar_full + 8);
        t_start = gtime32();
        TRACE(43);
    }

    if (warp == 8) {
        if (lane == 0) {
            asm volatile("prefetch.tensormap [%0];" :: "l"(&tm.wq));
            asm volatile("prefetch.tensormap [%0];" :: "l"(&tm.w1));
            asm volatile("prefetch.tensormap [%0];" :: "l"(&tm.v));
            asm volatile("prefetch.tensormap [%0];" :: "l"(&tm.wo));
            asm volatile("prefetch.tensormap [%0];" :: "l"(&tm.w2));
            mbar_init(bar_full + 16, 1); mbar_init(bar_full + 24, 1); mbar_init(bar_full + 32, 1);
            mbar_fence_init();
        }
        __syncwarp();
        bar_arrive288(2);
        const int i = lane;
        const int slot = i < NSLOT ? i : (i < 15 ? i - 10 : (i < 17 ? i - 15 : (i < 20 ? i - NSLOT : 8 + ((i - 20) >> 1))));
        const uint32_t f_empty = i < NSLOT ? 0u : (i < 15 ? bar_emptyA : bar_emptyK + (slot < 2 ? slot : slot - 3) * 8);
        const uint32_t f_bar = bar_full + i * 8;
        const uint32_t f_dst = sb + slot * SLOT + (i >= 20 ? (i & 1) * 8192 : 0);
        const uint32_t f_bytes = i >= 20 ? SLOT / 2 : (i == 19 ? 112 * 128 : SLOT);
        const bool f_bulk = i >= 5 && i <= 10;
        const void* f_ptr = i <= 3 ? (const void*)&tm.wq : i == 4 ? (const void*)&tm.w1
                          : f_bulk ? (const void*)(kcache + ((size_t)kvrow0 + (i - 3) * 64) * 128)
                          : i <= 18 ? (const void*)&tm.v : i == 19 ? (const void*)&tm.w2 : (const void*)&tm.wo;
        const int f_c0 = i <= 3 ? cta * 32 : i == 4 ? cta * 16 : i <= 18 ? 0 : cg * 64;
        const int f_c1 = i <= 3 ? (i - 2) * 256 : i == 4 ? 0 : i <= 18 ? (kvrow0 + (i - 11) * 64) * 2
                       : i == 19 ? kg * 112 : kg * 256 + (i - 20) * 64;
        const int phase = (((pace.scramble ? cta * 37 : cta) & 127) * pace.tau) >> 7;
        const int nt = max(i - pace.first_tail, 0);
        uint32_t f_due = pace.t0 + (i <= 19 ? phase + (i - 2) * pace.tau + nt * pace.tail_extra - (i > 4 ? pace.tau >> 3 : 0)
                                            : (phase >> 1) + ((18 * 8 - 2 + (i - 20) * 4) * pace.tau >> 3)
                                              + (((20 - pace.first_tail) * 2 + (i - 20)) * pace.tail_extra >> 1));
        f_due += __shfl_sync(0xffffffffu, t_start, 0);
        #pragma unroll 1
        for (int n = 2; n < NFILL; n++) {
            if (n == 5) bar_sync288(4);
            const uint32_t n_empty = __shfl_sync(0xffffffffu, f_empty, n), n_due = __shfl_sync(0xffffffffu, f_due, n);
            if (n_empty) mbar_wait0(n_empty);
            #pragma unroll 1
            for (uint32_t k = 0; k < SPIN_LIMIT && (int32_t)(gtime32() - n_due) < 0; k++) {}
            if (n == i && (i != 4 || cta < 112)) {
                mbar_expect_tx(f_bar, f_bytes);
                if (f_bulk) bulk_g2s(f_dst, f_ptr, SLOT, f_bar);
                else tma2d(f_dst, (const CUtensorMap*)f_ptr, f_c0, f_c1, f_bar);
                if (i == 4) tma2d(f_dst + 8192, (const CUtensorMap*)f_ptr, f_c0, 256, f_bar);
            }
        }
        return;
    }

    if (warp == 9) {
        const uint32_t cnt0 = ld_rlx(scr->cnt + hkv * 32);
        const uint4 pz = make_uint4(POISON, POISON, POISON, POISON);
        st_rlx4(scr->q + (lane >> 2) * 2048 + cta * 16 + (lane & 3) * 4, pz);
        if (lane < 16 && cta < 112) st_rlx4(scr->h + cta * 64 + lane * 4, pz);
        if (lane < 2) st_rlx4(scr->st + cta * 8 + lane * 4, pz);
        st_rlx4(scr->o + cta * 256 + lane * 4, pz);
        st_rlx4(scr->o + cta * 256 + 128 + lane * 4, pz);
        if (lane < 16) st_rlx4(reinterpret_cast<uint32_t*>(scr->acc) + cta * 64 + lane * 4, make_uint4(0u, 0u, 0u, 0u));
        __syncwarp();
        bar_arrive288(3);
        const uint32_t target = (cnt0 & ~15u) + 16u;
        if (lane == 0) {
            TRACE(11);
            asm volatile("fence.acq_rel.gpu;" ::: "memory");
            TRACE(12);
            asm volatile("red.relaxed.gpu.global.add.u32 [%0], 1;" :: "l"(scr->cnt + hkv * 32) : "memory");
            #pragma unroll 1
            for (uint32_t n = 0; (int32_t)(ld_acq(scr->cnt + hkv * 32) - target) < 0; n++) if (n > SPIN_LIMIT) __trap();
            TRACE(3);
        }
        __syncwarp();
        bar_sync288(5);
        mbar_wait0(bar_emptyA);
        if (pace.qdelay) __nanosleep(pace.qdelay);
        {
            const uint32_t* pq = scr->q + bb * 2048 + hkv * 256 + lane * 4;
            uint4 v0, v1;
            #pragma unroll 1
            for (uint32_t n = 0; ; n++) {
                v0 = ld_rlx4(pq); v1 = ld_rlx4(pq + 128);
                if (!__any_sync(0xffffffffu, has_poison(v0) || has_poison(v1))) break;
                if (n > SPIN_LIMIT) __trap();
            }
            const uint32_t a = sb + SM_Q + (lane >> 4) * 272 + (lane & 15) * 16;
            sts128(a, v0); sts128(a + 544, v1);
            __syncwarp();
            if (lane == 0) { mbar_arrive(bar_q); TRACE(23); }
        }
        #pragma unroll 1
        for (uint32_t n = 0; __any_sync(0xffffffffu, (int32_t)(ld_acq(scr->cnt + (lane & 7) * 32) - target) < 0); n++)
            if (n > SPIN_LIMIT) __trap();
        if (lane == 0) TRACE(20);
        mbar_wait0(bar_full + 12 * 8);
        {
            const uint32_t* p3 = lane < 16 ? scr->h + kg * 448 + 384 + lane * 4 : scr->st + (cta ^ 1) * 8 + (lane & 1) * 4;
            uint4 v[4];
            #pragma unroll 1
            for (uint32_t n = 0; ; n++) {
                #pragma unroll
                for (int i = 0; i < 3; i++) v[i] = ld_rlx4(scr->h + kg * 448 + i * 128 + lane * 4);
                v[3] = ld_rlx4(p3);
                if (!__any_sync(0xffffffffu, has_poison(v[0]) || has_poison(v[1]) || has_poison(v[2]) || has_poison(v[3]))) break;
                if (n > SPIN_LIMIT) __trap();
            }
            #pragma unroll
            for (int i = 0; i < 3; i++) sts128(sb + SM_H + i * 512 + lane * 16, v[i]);
            if (lane < 18) sts128(lane < 16 ? sb + SM_H + 1536 + lane * 16 : sb + SM_ST + (lane & 1) * 16, v[3]);
        }
        __syncwarp();
        if (lane == 0) { mbar_arrive(bar_st); TRACE(32); }
        return;
    }

    const uint4 xa = *reinterpret_cast<const uint4*>(x + warp * 512 + lane * 8);
    const uint4 xb = *reinterpret_cast<const uint4*>(x + warp * 512 + 256 + lane * 8);
    if (lane == 0) {
        #pragma unroll 1
        for (int j = 5 + warp; j < NBAR; j += 8) mbar_init(bar_full + j * 8, 1);
        mbar_fence_init();
    }
    __syncwarp();
    bar_arrive288(4);
    bar_arrive288(5);
    if (tid == 0) TRACE(13);
    {
        float xv[16];
        const uint32_t xw[8] = {xa.x, xa.y, xa.z, xa.w, xb.x, xb.y, xb.z, xb.w};
        #pragma unroll
        for (int i = 0; i < 8; i++) { xv[2 * i] = bf_lo(xw[i]); xv[2 * i + 1] = bf_hi(xw[i]); }
        float s = 0.f;
        #pragma unroll
        for (int i = 0; i < 16; i++) s += xv[i];
        #pragma unroll
        for (int o = 16; o; o >>= 1) s += __shfl_xor_sync(0xffffffffu, s, o);
        const float mean = s * (1.f / 512.f);
        if (tid == 0) TRACE(14);
        float q = 0.f;
        #pragma unroll
        for (int i = 0; i < 16; i++) { const float d = xv[i] - mean; q += d * d; }
        #pragma unroll
        for (int o = 16; o; o >>= 1) q += __shfl_xor_sync(0xffffffffu, q, o);
        const float mb = bf16r(mean);
        const float den = bf16r(sqrt_approx(bf16r(bf16r(q * (1.f / 512.f)) + 1e-5f)));
        uint32_t o[8];
        #pragma unroll
        for (int i = 0; i < 8; i++)
            o[i] = pack_bf16(__fdividef(bf16r(xv[2 * i] - mb), den), __fdividef(bf16r(xv[2 * i + 1] - mb), den));
        sts128(sb + SM_XN + warp * 1040 + lane * 16, make_uint4(o[0], o[1], o[2], o[3]));
        sts128(sb + SM_XN + warp * 1040 + 512 + lane * 16, make_uint4(o[4], o[5], o[6], o[7]));
    }
    if (tid == 0) TRACE(15);
    bar_sync288(2);
    bar_ln_done();
    if (tid == 0) TRACE(0);

    {
        uint32_t xf[4][2];
        #pragma unroll
        for (int s = 0; s < 4; s++) {
            const uint32_t a = sb + SM_XN + g * 1040 + (warp * 64 + s * 16 + 2 * t) * 2;
            xf[s][0] = lds32(a); xf[s][1] = lds32(a + 16);
        }
        float acc[3][4] = {};
        const int mi = lane >> 3, rr = lane & 7;
        const int krow = (warp & 3) * 64 + (mi >> 1) * 8 + rr;
        mbar_wait0(bar_full + (2 + (warp >> 2)) * 8);
        if (tid == 0) TRACE(16);
        if (tid == 128) TRACE(17);
        #pragma unroll
        for (int s = 0; s < 4; s++) {
            const int r = krow + s * 16;
            #pragma unroll
            for (int mt = 0; mt < 2; mt++) {
                uint32_t a[4];
                ldsm_x4_t(a, sb + (2 + (warp >> 2)) * SLOT + r * 64 + (((2 * mt + (mi & 1)) ^ ((r >> 1) & 3)) << 4));
                mma16816(acc[mt], a[0], a[1], a[2], a[3], xf[s][0], xf[s][1]);
            }
        }
        if (cta < 112) {
            mbar_wait0(bar_full + 4 * 8);
            if (tid == 0) TRACE(18);
            #pragma unroll
            for (int s = 0; s < 4; s++) {
                const int r = (warp >> 2) * 256 + krow + s * 16;
                uint32_t a[4];
                ldsm_x4_t(a, sb + 4 * SLOT + r * 32 + (((mi & 1) ^ ((r >> 2) & 1)) << 4));
                mma16816(acc[2], a[0], a[1], a[2], a[3], xf[s][0], xf[s][1]);
            }
        }
        #pragma unroll
        for (int mt = 0; mt < 3; mt++)
            sts128(sb + SM_RED + (warp * 3 + mt) * 512 + lane * 16,
                   make_uint4(__float_as_uint(acc[mt][0]), __float_as_uint(acc[mt][1]), __float_as_uint(acc[mt][2]), __float_as_uint(acc[mt][3])));
    }
    bar_consumers();
    if (tid == 0) { TRACE(1); mbar_arrive(bar_emptyA); }
    if (tid < 192) {
        const int tile = tid < 128 ? ((tid >> 3) & 1) : 2;
        const int b = tid < 128 ? (tid >> 4) : ((tid - 128) >> 3);
        const int j = tid & 7;
        const uint32_t a = sb + SM_RED + tile * 512 + (4 * ((2 * j) & 7) + (b >> 1)) * 16 + (2 * (j >> 2) + (b & 1)) * 4;
        float v0 = 0.f, v1 = 0.f;
        #pragma unroll
        for (int w = 0; w < 8; w++) { v0 += lds32f(a + w * 1536); v1 += lds32f(a + w * 1536 + 64); }
        if (tid < 128) {
            st_rlx(scr->q + b * 2048 + cta * 16 + (tid & 15), unpoison(pack_bf16(v0, v1)));
        } else if (cta < 112) {
            v0 = bf16r(v0); v1 = bf16r(v1);
            v0 = __fdividef(v0, 1.f + __expf(-v0));
            v1 = __fdividef(v1, 1.f + __expf(-v1));
            st_rlx(scr->h + cta * 64 + b * 8 + 2 * (j & 3) + (j >> 2), unpoison(pack_bf16(v0, v1)));
        }
    }
    if (tid == 0) TRACE(2);

    float sc[4][4] = {};
    {
        uint4 qf[4];
        mbar_wait0(bar_q);
        #pragma unroll
        for (int j = 0; j < 4; j++) qf[j] = lds128(sb + SM_Q + (g & 3) * 272 + (4 * (j ^ (g >> 2)) + t) * 16);
        const int fill = warp < 2 ? warp : warp + 3;
        mbar_wait0(bar_full + fill * 8);
        if (tid == 0 && qf[3].w != 0x12345) TRACE(19);
        const uint32_t kb = sb + fill * SLOT + g * 256 + t * 16;
        #pragma unroll
        for (int j = 0; j < 4; j++) {
            #pragma unroll
            for (int mt = 0; mt < 4; mt++) {
                const uint32_t a = kb + mt * 4096 + ((j ^ (g & 1)) << 6);
                const uint4 lo = lds128(a), hi = lds128(a + 2048);
                mma16816(sc[mt], lo.x, hi.x, lo.y, hi.y, qf[j].x, qf[j].y);
                mma16816(sc[mt], lo.z, hi.z, lo.w, hi.w, qf[j].z, qf[j].w);
            }
        }
        __syncwarp();
        if (lane == 0 && warp < 7) mbar_arrive(bar_emptyK + warp * 8);
    }
    if (tid == 0) TRACE(4);
    if (tid == 224) TRACE(5);
    const bool valid = (t >> 1) == (g & 1);
    const int h0 = 2 * (t & 1);
    {
        float m0 = -INFINITY, m1 = -INFINITY;
        #pragma unroll
        for (int mt = 0; mt < 4; mt++) {
            #pragma unroll
            for (int i = 0; i < 4; i++) sc[mt][i] = bf16r(bf16r(sc[mt][i]) * 0.08838834764831845f);
            m0 = fmaxf(m0, fmaxf(sc[mt][0], sc[mt][2]));
            m1 = fmaxf(m1, fmaxf(sc[mt][1], sc[mt][3]));
        }
        if (!valid) { m0 = -INFINITY; m1 = -INFINITY; }
        #pragma unroll
        for (int o = 2; o <= 16; o <<= 1) {
            m0 = fmaxf(m0, __shfl_xor_sync(0xffffffffu, m0, o));
            m1 = fmaxf(m1, __shfl_xor_sync(0xffffffffu, m1, o));
        }
        if (lane < 2) { sts32f(sb + SM_WMAX + warp * 16 + h0 * 4, m0); sts32f(sb + SM_WMAX + warp * 16 + h0 * 4 + 4, m1); }
    }
    bar_consumers();
    if (tid == 0) TRACE(21);
    float mloc0 = -INFINITY, mloc1 = -INFINITY;
    {
        #pragma unroll
        for (int w = 0; w < 8; w++) {
            mloc0 = fmaxf(mloc0, lds32f(sb + SM_WMAX + w * 16 + h0 * 4));
            mloc1 = fmaxf(mloc1, lds32f(sb + SM_WMAX + w * 16 + h0 * 4 + 4));
        }
        const float L2E = 1.4426950408889634f;
        float l0 = 0.f, l1 = 0.f;
        const uint32_t pa = sb + SM_P + (h0 * 260 + warp * 32 + (g & 3) * 8 + (g >> 2)) * 4;
        #pragma unroll
        for (int mt = 0; mt < 4; mt++) {
            const float p0 = ex2((sc[mt][0] - mloc0) * L2E), p2 = ex2((sc[mt][2] - mloc0) * L2E);
            const float p1 = ex2((sc[mt][1] - mloc1) * L2E), p3 = ex2((sc[mt][3] - mloc1) * L2E);
            l0 += p0 + p2; l1 += p1 + p3;
            if (valid) { sts32(pa + mt * 8, pack_bf16(p0, p2)); sts32(pa + 1040 + mt * 8, pack_bf16(p1, p3)); }
        }
        if (!valid) { l0 = 0.f; l1 = 0.f; }
        #pragma unroll
        for (int o = 2; o <= 16; o <<= 1) {
            l0 += __shfl_xor_sync(0xffffffffu, l0, o);
            l1 += __shfl_xor_sync(0xffffffffu, l1, o);
        }
        if (lane < 2) { sts32f(sb + SM_WSUM + warp * 16 + h0 * 4, l0); sts32f(sb + SM_WSUM + warp * 16 + h0 * 4 + 4, l1); }
    }
    if (tid == 0) TRACE(22);
    bar_consumers();
    if (tid == 0) TRACE(6);
    float lloc0 = 0.f, lloc1 = 0.f;
    #pragma unroll
    for (int w = 0; w < 8; w++) {
        lloc0 += lds32f(sb + SM_WSUM + w * 16 + h0 * 4);
        lloc1 += lds32f(sb + SM_WSUM + w * 16 + h0 * 4 + 4);
    }
    if (tid < 2) {
        st_rlx(scr->st + cta * 8 + h0, unpoison(__float_as_uint(mloc0)));
        st_rlx(scr->st + cta * 8 + h0 + 1, unpoison(__float_as_uint(mloc1)));
        st_rlx(scr->st + cta * 8 + 4 + h0, unpoison(__float_as_uint(lloc0)));
        st_rlx(scr->st + cta * 8 + 4 + h0 + 1, unpoison(__float_as_uint(lloc1)));
    }

    float oa[2][4] = {};
    float scale0 = 0.f, scale1 = 0.f;
    {
        const int mi = lane >> 3, rr = lane & 7;
        const int key = (rr >> 1) + 4 * (mi >> 1) + 8 * (rr & 1);
        const int rowp = 2 * key + (warp >> 2);
        const uint32_t voff = rowp * 128 + (((2 * (warp & 3) + (mi & 1)) ^ (rowp & 7)) << 4);
        #pragma unroll 1
        for (int vc = 0; vc < 8; vc++) {
            uint4 p0 = make_uint4(0u, 0u, 0u, 0u), p1 = p0;
            if (g < 4) {
                const uint32_t a = sb + SM_P + (g * 260 + vc * 32 + t * 8) * 4;
                p0 = lds128(a); p1 = lds128(a + 16);
            }
            if (vc == 7) {
                mbar_wait0(bar_st);
                const float L2E = 1.4426950408889634f;
                const float mo0 = lds32f(sb + SM_ST + h0 * 4), mo1 = lds32f(sb + SM_ST + h0 * 4 + 4);
                const float mg0 = fmaxf(mloc0, mo0), mg1 = fmaxf(mloc1, mo1);
                const float e0 = ex2((mloc0 - mg0) * L2E), e1 = ex2((mloc1 - mg1) * L2E);
                scale0 = __fdividef(e0, lloc0 * e0 + lds32f(sb + SM_ST + 16 + h0 * 4) * ex2((mo0 - mg0) * L2E));
                scale1 = __fdividef(e1, lloc1 * e1 + lds32f(sb + SM_ST + 20 + h0 * 4) * ex2((mo1 - mg1) * L2E));
            }
            const int fill = 11 + vc, slot = vc == 0 ? 11 : (vc < 4 ? vc + 1 : (vc < 6 ? vc - 4 : vc - 1));
            mbar_wait0(bar_full + fill * 8);
            if (tid == 0) TRACE(24 + vc);
            const uint32_t vb = sb + slot * SLOT + voff;
            uint32_t a0[4], a1[4], a2[4], a3[4];
            ldsm_x4_t(a0, vb); ldsm_x4_t(a1, vb + 4096); ldsm_x4_t(a2, vb + 8192); ldsm_x4_t(a3, vb + 12288);
            mma16816(oa[0], a0[0], a0[1], a0[2], a0[3], p0.x, p0.y);
            mma16816(oa[1], a1[0], a1[1], a1[2], a1[3], p0.z, p0.w);
            mma16816(oa[0], a2[0], a2[1], a2[2], a2[3], p1.x, p1.y);
            mma16816(oa[1], a3[0], a3[1], a3[2], a3[3], p1.z, p1.w);
        }
        if (tid == 0) TRACE(7);
        const uint32_t lo = pack_bf16((oa[0][0] + oa[1][0]) * scale0, (oa[0][1] + oa[1][1]) * scale1);
        const uint32_t hi = pack_bf16((oa[0][2] + oa[1][2]) * scale0, (oa[0][3] + oa[1][3]) * scale1);
        const bool odd = g & 1;
        const uint32_t y = __shfl_xor_sync(0xffffffffu, odd ? lo : hi, 4);
        const uint32_t first = odd ? y : lo, second = odd ? hi : y;
        if (t < 2) {
            uint32_t* po = scr->o + cta * 256 + h0 * 64 + (warp >> 1) * 16 + (g >> 1) * 4 + (warp & 1) * 2 + (g & 1);
            st_rlx(po, unpoison(__byte_perm(first, second, 0x5410)));
            st_rlx(po + 64, unpoison(__byte_perm(first, second, 0x7632)));
        }
        if (tid == 0) TRACE(49);
    }

    {
        const uint32_t* po = scr->o + (hkv * 16 + warp * 2) * 256 + (kg & 1) * 128 + lane * 4;
        keep64(po);
        float acc[4][4] = {};
        uint32_t wa[3][4][4];
        const int mi = lane >> 3, rr = lane & 7;
        uint32_t wb = sb + 8 * SLOT + ((mi >> 1) * 8 + rr) * 128 + (((2 * warp + (mi & 1)) ^ rr) << 4);
        const int ocol = 64 * cg + 16 * warp + g;
        float* pacc = scr->acc + (cg * 4 + warp) * 256 + lane * 4;
        __nv_bfloat16* pout = out + 2 * t * 512 + ocol;
        float x0 = 0.f, x1 = 0.f, x2 = 0.f, x3 = 0.f;
        keep32(wb); keep64(pacc); keep64(pout);
        if (warp < 4) {
            const __nv_bfloat16* px = x + 2 * t * 512 + ocol;
            const __nv_bfloat16 b0 = px[0], b1 = px[512], b2 = px[8], b3 = px[520];
            mbar_wait0(bar_full + 19 * 8);
            if (tid == 0) TRACE(8);
            #pragma unroll
            for (int i = 0; i < 7; i++) {
                uint32_t a[4];
                ldsm_x4_t(a, wb - SLOT + i * 2048);
                const uint32_t ha = sb + SM_H + i * 256 + lane * 8;
                mma16816(acc[i & 3], a[0], a[1], a[2], a[3], lds32(ha), lds32(ha + 4));
            }
            x0 = __bfloat162float(b0); x1 = __bfloat162float(b1); x2 = __bfloat162float(b2); x3 = __bfloat162float(b3);
            keepf(x0); keepf(x1); keepf(x2); keepf(x3);
        }
        mbar_wait0(bar_full + pace.opoll * 8);
        uint4 v0 = ld_rlx4(po), v1 = ld_rlx4(po + 256);
        if (tid == 0) TRACE(34);
        if (warp < 4) {
            #pragma unroll
            for (int pc = 0; pc < 3; pc++) {
                mbar_wait0(bar_full + (20 + pc) * 8);
                #pragma unroll
                for (int k = 0; k < 4; k++) ldsm_x4_t(wa[pc][k], wb + pc * 8192 + k * 2048);
            }
        }
        #pragma unroll 1
        for (uint32_t n = 0; ; n++) {
            const bool b0 = __any_sync(0xffffffffu, has_poison(v0)), b1 = __any_sync(0xffffffffu, has_poison(v1));
            if (!b0 && !b1) break;
            if (b0) v0 = ld_rlx4(po);
            if (b1) v1 = ld_rlx4(po + 256);
            if (n > SPIN_LIMIT) __trap();
        }
        sts128(sb + SM_O + warp * 576 + lane * 16,
               make_uint4(hadd2_bf16(v0.x, v1.x), hadd2_bf16(v0.y, v1.y), hadd2_bf16(v0.z, v1.z), hadd2_bf16(v0.w, v1.w)));
        if (warp >= 4) { asm volatile("bar.arrive 1, 256;" ::: "memory"); return; }
        bar_consumers();
        if (tid == 0) { TRACE(9); TRACE(48); }
        uint4 of[8];
        #pragma unroll
        for (int i = 0; i < 8; i++) of[i] = lds128(sb + SM_O + g * 576 + i * 64 + t * 16);
        #pragma unroll
        for (int pc = 0; pc < 3; pc++) {
            mma16816(acc[0], wa[pc][0][0], wa[pc][0][1], wa[pc][0][2], wa[pc][0][3], of[2 * pc].x, of[2 * pc].y);
            mma16816(acc[1], wa[pc][1][0], wa[pc][1][1], wa[pc][1][2], wa[pc][1][3], of[2 * pc].z, of[2 * pc].w);
            mma16816(acc[2], wa[pc][2][0], wa[pc][2][1], wa[pc][2][2], wa[pc][2][3], of[2 * pc + 1].x, of[2 * pc + 1].y);
            mma16816(acc[3], wa[pc][3][0], wa[pc][3][1], wa[pc][3][2], wa[pc][3][3], of[2 * pc + 1].z, of[2 * pc + 1].w);
        }
        {
            uint32_t a0[4], a1[4], a2[4], a3[4];
            mbar_wait0(bar_full + 23 * 8);
            ldsm_x4_t(a0, wb + 24576); ldsm_x4_t(a1, wb + 24576 + 2048); ldsm_x4_t(a2, wb + 24576 + 4096); ldsm_x4_t(a3, wb + 24576 + 6144);
            mma16816(acc[0], a0[0], a0[1], a0[2], a0[3], of[6].x, of[6].y);
            mma16816(acc[1], a1[0], a1[1], a1[2], a1[3], of[6].z, of[6].w);
            mma16816(acc[2], a2[0], a2[1], a2[2], a2[3], of[7].x, of[7].y);
            mma16816(acc[3], a3[0], a3[1], a3[2], a3[3], of[7].z, of[7].w);
        }
        float r[4];
        #pragma unroll
        for (int i = 0; i < 4; i++) r[i] = (acc[0][i] + acc[1][i]) + (acc[2][i] + acc[3][i]);
        float4 o0, o1;
        asm volatile("atom.relaxed.gpu.global.add.v4.f32 {%0,%1,%2,%3}, [%4], {%5,%6,%7,%8};"
                     : "=f"(o0.x), "=f"(o0.y), "=f"(o0.z), "=f"(o0.w) : "l"(pacc), "f"(r[0]), "f"(r[1]), "f"(1.f), "f"(0.f) : "memory");
        asm volatile("atom.relaxed.gpu.global.add.v4.f32 {%0,%1,%2,%3}, [%4], {%5,%6,%7,%8};"
                     : "=f"(o1.x), "=f"(o1.y), "=f"(o1.z), "=f"(o1.w) : "l"(pacc + 128), "f"(r[2]), "f"(r[3]), "f"(1.f), "f"(0.f) : "memory");
        if (tid == 0) TRACE(10);
        r[0] += x0; r[1] += x1; r[2] += x2; r[3] += x3;
        if (o0.z == 15.f) {
            pout[0] = __float2bfloat16_rn(o0.x + r[0]);
            pout[512] = __float2bfloat16_rn(o0.y + r[1]);
        }
        if (o1.z == 15.f) {
            pout[8] = __float2bfloat16_rn(o1.x + r[2]);
            pout[520] = __float2bfloat16_rn(o1.y + r[3]);
        }
    }
}

typedef CUresult (*EncodeTiledFn)(CUtensorMap*, CUtensorMapDataType, cuuint32_t, void*, const cuuint64_t*, const cuuint64_t*,
                                  const cuuint32_t*, const cuuint32_t*, CUtensorMapInterleave, CUtensorMapSwizzle,
                                  CUtensorMapL2promotion, CUtensorMapFloatOOBfill);

void make_map(EncodeTiledFn enc, CUtensorMap* m, const void* base, uint64_t cols, uint64_t rows, uint32_t box_cols,
              uint32_t box_rows, CUtensorMapSwizzle sw) {
    cuuint64_t gd[2] = {cols, rows};
    cuuint64_t gs[1] = {cols * 2};
    cuuint32_t bd[2] = {box_cols, box_rows};
    cuuint32_t es[2] = {1, 1};
    enc(m, CU_TENSOR_MAP_DATA_TYPE_BFLOAT16, 2, const_cast<void*>(base), gd, gs, bd, es, CU_TENSOR_MAP_INTERLEAVE_NONE, sw,
        CU_TENSOR_MAP_L2_PROMOTION_L2_256B, CU_TENSOR_MAP_FLOAT_OOB_FILL_NONE);
}

}

extern "C" void kernel_launch(void* const* d_in, const int* in_sizes, int n_in, void* d_out, int out_size) {
    (void)in_sizes; (void)n_in; (void)out_size;
    static EncodeTiledFn enc = nullptr;
    static Scratch* scr = nullptr;
    if (!enc) {
        cudaGetSymbolAddress((void**)&scr, g_scratch);
        void* fn = nullptr;
        cudaDriverEntryPointQueryResult qr;
        cudaGetDriverEntryPoint("cuTensorMapEncodeTiled", &fn, cudaEnableDefault, &qr);
        enc = (EncodeTiledFn)fn;
        cudaFuncSetAttribute(fused_decode_kernel, cudaFuncAttributeMaxDynamicSharedMemorySize, SMEM_BYTES);
    }
    TMaps tm;
    make_map(enc, &tm.wq, d_in[3], 4096, 512, 32, 256, CU_TENSOR_MAP_SWIZZLE_64B);
    make_map(enc, &tm.w1, d_in[6], 1792, 512, 16, 256, CU_TENSOR_MAP_SWIZZLE_32B);
    make_map(enc, &tm.v, d_in[2], 64, 8ull * 8 * 4096 * 2, 64, 128, CU_TENSOR_MAP_SWIZZLE_128B);
    make_map(enc, &tm.wo, d_in[4], 512, 4096, 64, 64, CU_TENSOR_MAP_SWIZZLE_128B);
    make_map(enc, &tm.w2, d_in[7], 512, 1792, 64, 112, CU_TENSOR_MAP_SWIZZLE_128B);
    fused_decode_kernel<<<NCTA, NTHREADS, SMEM_BYTES, cudaStreamPerThread>>>(
        (const __nv_bfloat16*)d_in[1], (const __nv_bfloat16*)d_in[0], (__nv_bfloat16*)d_out, scr, g_pace, tm);
}
```

```cpp
#include <cuda_runtime.h>
#include <cuda_bf16.h>
#include <cuda.h>
#include <stdint.h>

namespace {

constexpr int NCTA = 128;
constexpr int NTHREADS = 320;
constexpr int SLOT = 16384;
constexpr int NSLOT = 12;
constexpr int NFILL = 24;
constexpr uint32_t POISON = 0xFFFFFFFFu;
constexpr uint32_t SPIN_LIMIT = 1u << 22;

struct Pace { int t0, tau, tail_extra, first_tail, opoll, scramble, qdelay, rot, pf; };
constexpr Pace g_pace = {500, 655, 70, 16, 20, 0, 300, 200, 0};

constexpr int SM_RING = 0;
constexpr int SM_XN = NSLOT * SLOT;
constexpr int SM_RED = SM_XN + 8 * 1040;
constexpr int SM_P = SM_RED + 8 * 3 * 512;
constexpr int SM_WMAX = SM_P + 4 * 260 * 4;
constexpr int SM_WSUM = SM_WMAX + 128;
constexpr int SM_ST = SM_WSUM + 128;
constexpr int SM_Q = SM_ST + 32;
constexpr int SM_H = SM_Q + 4 * 272;
constexpr int SM_O = SM_RED;
constexpr int SM_BAR = SM_H + 7 * 256;
constexpr int NBAR = NFILL + 7 + 4;
constexpr int SM_TOTAL = SM_BAR + NBAR * 8;
constexpr int SMEM_BYTES = SM_TOTAL + 1024;

struct TMaps { CUtensorMap wq, w1, v, wo, w2; };

struct Scratch {
    float acc[8 * 4 * 2 * 128];
    uint32_t o[NCTA * 256];
    uint32_t q[8 * 2048];
    uint32_t h[112 * 64];
    uint32_t st[NCTA * 8];
    uint32_t cnt[8 * 32];
};
__device__ __align__(128) Scratch g_scratch;

#define TRACE(i) do {} while (0)

__device__ __forceinline__ uint32_t clk32() { uint32_t c; asm volatile("mov.u32 %0, %clock;" : "=r"(c)); return c; }
__device__ __forceinline__ uint32_t gtime32() { uint32_t c; asm volatile("mov.u32 %0, %globaltimer_lo;" : "=r"(c)); return c; }
__device__ __forceinline__ uint32_t smem_u32(const void* p) { return (uint32_t)__cvta_generic_to_shared(p); }

__device__ __forceinline__ void mbar_init(uint32_t bar, uint32_t cnt) {
    asm volatile("mbarrier.init.shared::cta.b64 [%0], %1;" :: "r"(bar), "r"(cnt) : "memory");
}
__device__ __forceinline__ void mbar_fence_init() { asm volatile("fence.mbarrier_init.release.cluster;" ::: "memory"); }
__device__ __forceinline__ void mbar_expect_tx(uint32_t bar, uint32_t bytes) {
    asm volatile("mbarrier.arrive.expect_tx.shared::cta.b64 _, [%0], %1;" :: "r"(bar), "r"(bytes) : "memory");
}
__device__ __forceinline__ void mbar_arrive(uint32_t bar) {
    asm volatile("mbarrier.arrive.shared::cta.b64 _, [%0];" :: "r"(bar) : "memory");
}
__device__ __forceinline__ void mbar_wait0(uint32_t bar) {
    #pragma unroll 1
    for (uint32_t i = 0; i < SPIN_LIMIT; i++) {
        uint32_t ok;
        asm volatile("{\n.reg .pred p;\nmbarrier.try_wait.parity.shared::cta.b64 p, [%1], 0;\nselp.u32 %0, 1, 0, p;\n}"
                     : "=r"(ok) : "r"(bar) : "memory");
        if (ok) return;
    }
    __trap();
}
constexpr uint64_t EVICT_FIRST = 0x12F0000000000000ull;
__device__ __forceinline__ bool mbar_test0(uint32_t bar) {
    uint32_t ok;
    asm volatile("{\n.reg .pred p;\nmbarrier.test_wait.parity.shared::cta.b64 p, [%1], 0;\nselp.u32 %0, 1, 0, p;\n}"
                 : "=r"(ok) : "r"(bar) : "memory");
    return ok;
}
__device__ __forceinline__ void bulk_g2s(uint32_t dst, const void* src, uint32_t bytes, uint32_t bar) {
    asm volatile("cp.async.bulk.shared::cluster.global.mbarrier::complete_tx::bytes.L2::cache_hint [%0], [%1], %2, [%3], %4;"
                 :: "r"(dst), "l"(src), "r"(bytes), "r"(bar), "l"(EVICT_FIRST) : "memory");
}
__device__ __forceinline__ void tma2d(uint32_t dst, const CUtensorMap* tm, int c0, int c1, uint32_t bar) {
    asm volatile("cp.async.bulk.tensor.2d.shared::cluster.global.mbarrier::complete_tx::bytes.L2::cache_hint [%0], [%1, {%3, %4}], [%2], %5;"
                 :: "r"(dst), "l"(tm), "r"(bar), "r"(c0), "r"(c1), "l"(EVICT_FIRST) : "memory");
}
__device__ __forceinline__ void bar_consumers() { asm volatile("bar.sync 1, 256;" ::: "memory"); }
__device__ __forceinline__ void bar_sync288(int id) { asm volatile("bar.sync %0, 288;" :: "r"(id) : "memory"); }
__device__ __forceinline__ void bar_arrive288(int id) { asm volatile("bar.arrive %0, 288;" :: "r"(id) : "memory"); }
template <typename T> __device__ __forceinline__ void keep64(T*& p) { asm volatile("" : "+l"(p)); }
__device__ __forceinline__ void keep32(uint32_t& v) { asm volatile("" : "+r"(v)); }
__device__ __forceinline__ void keepf(float& v) { asm volatile("" : "+f"(v)); }
__device__ __forceinline__ uint32_t hadd2_bf16(uint32_t a, uint32_t b) {
    uint32_t r; asm("add.rn.bf16x2 %0, %1, %2;" : "=r"(r) : "r"(a), "r"(b)); return r;
}
__device__ __forceinline__ void bar_ln_done() { asm volatile("bar.sync 3, 288;" ::: "memory"); }

__device__ __forceinline__ uint4 lds128(uint32_t a) {
    uint4 v; asm volatile("ld.shared.v4.u32 {%0,%1,%2,%3}, [%4];" : "=r"(v.x), "=r"(v.y), "=r"(v.z), "=r"(v.w) : "r"(a)); return v;
}
__device__ __forceinline__ uint32_t lds32(uint32_t a) { uint32_t v; asm volatile("ld.shared.u32 %0, [%1];" : "=r"(v) : "r"(a)); return v; }
__device__ __forceinline__ float lds32f(uint32_t a) { float v; asm volatile("ld.shared.f32 %0, [%1];" : "=f"(v) : "r"(a)); return v; }
__device__ __forceinline__ void sts32(uint32_t a, uint32_t v) { asm volatile("st.shared.u32 [%0], %1;" :: "r"(a), "r"(v) : "memory"); }
__device__ __forceinline__ void sts32f(uint32_t a, float v) { asm volatile("st.shared.f32 [%0], %1;" :: "r"(a), "f"(v) : "memory"); }
__device__ __forceinline__ void sts64(uint32_t a, uint32_t x, uint32_t y) {
    asm volatile("st.shared.v2.u32 [%0], {%1,%2};" :: "r"(a), "r"(x), "r"(y) : "memory");
}
__device__ __forceinline__ void sts128(uint32_t a, uint4 v) {
    asm volatile("st.shared.v4.u32 [%0], {%1,%2,%3,%4};" :: "r"(a), "r"(v.x), "r"(v.y), "r"(v.z), "r"(v.w) : "memory");
}
__device__ __forceinline__ void ldsm_x4_t(uint32_t (&r)[4], uint32_t a) {
    asm volatile("ldmatrix.sync.aligned.m8n8.x4.trans.shared.b16 {%0,%1,%2,%3}, [%4];"
                 : "=r"(r[0]), "=r"(r[1]), "=r"(r[2]), "=r"(r[3]) : "r"(a));
}
__device__ __forceinline__ void mma16816(float (&c)[4], uint32_t a0, uint32_t a1, uint32_t a2, uint32_t a3, uint32_t b0, uint32_t b1) {
    asm volatile("mma.sync.aligned.m16n8k16.row.col.f32.bf16.bf16.f32 {%0,%1,%2,%3}, {%4,%5,%6,%7}, {%8,%9}, {%0,%1,%2,%3};"
                 : "+f"(c[0]), "+f"(c[1]), "+f"(c[2]), "+f"(c[3]) : "r"(a0), "r"(a1), "r"(a2), "r"(a3), "r"(b0), "r"(b1));
}

__device__ __forceinline__ uint32_t ld_rlx(const uint32_t* p) {
    uint32_t v; asm volatile("ld.relaxed.gpu.global.u32 %0, [%1];" : "=r"(v) : "l"(p) : "memory"); return v;
}
__device__ __forceinline__ uint32_t ld_acq(const uint32_t* p) {
    uint32_t v; asm volatile("ld.acquire.gpu.global.u32 %0, [%1];" : "=r"(v) : "l"(p) : "memory"); return v;
}
__device__ __forceinline__ uint2 ld_rlx2(const uint32_t* p) {
    uint2 v; asm volatile("ld.relaxed.gpu.global.v2.u32 {%0,%1}, [%2];" : "=r"(v.x), "=r"(v.y) : "l"(p) : "memory"); return v;
}
__device__ __forceinline__ uint4 ld_rlx4(const uint32_t* p) {
    uint4 v; asm volatile("ld.relaxed.gpu.global.v4.u32 {%0,%1,%2,%3}, [%4];" : "=r"(v.x), "=r"(v.y), "=r"(v.z), "=r"(v.w) : "l"(p) : "memory"); return v;
}
__device__ __forceinline__ void st_rlx(uint32_t* p, uint32_t v) {
    asm volatile("st.relaxed.gpu.global.u32 [%0], %1;" :: "l"(p), "r"(v) : "memory");
}
__device__ __forceinline__ void st_rlx4(uint32_t* p, uint4 v) {
    asm volatile("st.relaxed.gpu.global.v4.u32 [%0], {%1,%2,%3,%4};" :: "l"(p), "r"(v.x), "r"(v.y), "r"(v.z), "r"(v.w) : "memory");
}
__device__ __forceinline__ bool has_poison(const uint4& v) {
    return v.x == POISON || v.y == POISON || v.z == POISON || v.w == POISON;
}
__device__ __forceinline__ uint32_t unpoison(uint32_t w) { return w == POISON ? 0x7FFFFFFFu : w; }

__device__ __forceinline__ float sqrt_approx(float x) { float r; asm("sqrt.approx.f32 %0, %1;" : "=f"(r) : "f"(x)); return r; }
__device__ __forceinline__ float ex2(float x) { float r; asm("ex2.approx.ftz.f32 %0, %1;" : "=f"(r) : "f"(x)); return r; }
__device__ __forceinline__ float bf16r(float x) { return __bfloat162float(__float2bfloat16_rn(x)); }
__device__ __forceinline__ uint32_t pack_bf16(float lo, float hi) {
    uint32_t r; asm("cvt.rn.bf16x2.f32 %0, %1, %2;" : "=r"(r) : "f"(hi), "f"(lo)); return r;
}
__device__ __forceinline__ float bf_lo(uint32_t w) { return __uint_as_float(w << 16); }
__device__ __forceinline__ float bf_hi(uint32_t w) { return __uint_as_float(w & 0xFFFF0000u); }

__global__ void __launch_bounds__(NTHREADS, 1)
fused_decode_kernel(const __nv_bfloat16* __restrict__ kcache, const __nv_bfloat16* __restrict__ x,
                    __nv_bfloat16* __restrict__ out, Scratch* __restrict__ scr,
                    const __grid_constant__ TMaps tm)
{
    constexpr Pace pace = g_pace;
    extern __shared__ uint8_t smem_raw[];
    const uint32_t sb = (smem_u32(smem_raw) + 1023u) & ~1023u;
    const int tid = threadIdx.x, warp = tid >> 5, lane = tid & 31;
    const int cta = blockIdx.x;
    const int hkv = cta >> 4, bb = (cta >> 1) & 7, half = cta & 1;
    const int kg = cta >> 3, cg = cta & 7;
    const int g = lane >> 2, t = lane & 3;
    const uint32_t bar_full = sb + SM_BAR, bar_emptyK = bar_full + NFILL * 8, bar_emptyA = bar_emptyK + 7 * 8;
    const uint32_t bar_q = bar_emptyA + 8, bar_st = bar_q + 8, bar_o = bar_st + 8;

    const int kvrow0 = (bb * 8 + hkv) * 4096 + 3072 + half * 512;
    auto chunk_row = [&](int j) { return kvrow0 + j * 64; };
    uint32_t t_start = 0;
#define PF_TID 288
#define PF_BYTES (2 * SLOT)
    if (tid == PF_TID)
        asm volatile("cp.async.bulk.prefetch.L2.global.L2::cache_hint [%0], %1, %2;"
                     :: "l"(kcache + (size_t)kvrow0 * 128), "r"(PF_BYTES), "l"(EVICT_FIRST) : "memory");
    if (tid == 256) {
        mbar_init(bar_full, 1);
        mbar_init(bar_full + 8, 1);
        mbar_fence_init();
        mbar_expect_tx(bar_full, SLOT);
        bulk_g2s(sb, kcache + (size_t)chunk_row(0) * 128, SLOT, bar_full);
        mbar_expect_tx(bar_full + 8, SLOT);
        bulk_g2s(sb + SLOT, kcache + (size_t)chunk_row(1) * 128, SLOT, bar_full + 8);
        t_start = gtime32();
        TRACE(43);
    }

    if (warp == 8) {
        if (lane == 0) {
            asm volatile("prefetch.tensormap [%0];" :: "l"(&tm.wq));
            asm volatile("prefetch.tensormap [%0];" :: "l"(&tm.w1));
            asm volatile("prefetch.tensormap [%0];" :: "l"(&tm.v));
            asm volatile("prefetch.tensormap [%0];" :: "l"(&tm.wo));
            asm volatile("prefetch.tensormap [%0];" :: "l"(&tm.w2));
            mbar_init(bar_full + 16, 1); mbar_init(bar_full + 24, 1); mbar_init(bar_full + 32, 1);
            mbar_fence_init();
        }
        __syncwarp();
        bar_arrive288(2);
        const int i = lane;
        const int slot = i < NSLOT ? i : (i < 15 ? i - 10 : (i < 17 ? i - 15 : (i < 20 ? i - NSLOT : 8 + ((i - 20) >> 1))));
        const uint32_t f_empty = i < NSLOT ? 0u : (i < 15 ? bar_emptyA : bar_emptyK + (slot < 2 ? slot : slot - 3) * 8);
        const uint32_t f_bar = bar_full + i * 8;
        const uint32_t f_dst = sb + slot * SLOT + (i >= 20 ? (i & 1) * 8192 : 0);
        const uint32_t f_bytes = i >= 20 ? SLOT / 2 : (i == 19 ? 112 * 128 : SLOT);
        const bool f_bulk = i >= 5 && i <= 10;
        const void* f_ptr = i <= 3 ? (const void*)&tm.wq : i == 4 ? (const void*)&tm.w1
                          : f_bulk ? (const void*)(kcache + (size_t)chunk_row((i - 3) & 7) * 128)
                          : i <= 18 ? (const void*)&tm.v : i == 19 ? (const void*)&tm.w2 : (const void*)&tm.wo;
        const int f_c0 = i <= 3 ? cta * 32 : i == 4 ? cta * 16 : i <= 18 ? 0 : cg * 64;
        const int f_c1 = i <= 3 ? (i - 2) * 256 : i == 4 ? 0 : i <= 18 ? chunk_row((i - 11) & 7) * 2
                       : i == 19 ? kg * 112 : kg * 256 + (i - 20) * 64;
        const int pidx = pace.scramble == 0 ? cta : pace.scramble == 1 ? (cta * 37) & 127 : pace.scramble == 2 ? 0
                       : pace.scramble == 3 ? (cta & ~15) : pace.scramble == 4 ? ((cta & 15) << 3) | (cta >> 4) : (cta & ~1);
        const int phase = (pidx * pace.tau) >> 7;
        const int nt = max(i - pace.first_tail, 0);
        uint32_t f_due = pace.t0 + (i <= 19 ? phase + (i - 2) * pace.tau + nt * pace.tail_extra - (i > 4 ? pace.tau >> 3 : 0)
                                            : (phase >> 1) + ((18 * 8 - 2 + (i - 20) * 4) * pace.tau >> 3)
                                              + (((20 - pace.first_tail) * 2 + (i - 20)) * pace.tail_extra >> 1));
        f_due += __shfl_sync(0xffffffffu, t_start, 0);
        #pragma unroll 1
        for (int n = 2; n < NFILL; n++) {
            if (n == 5) bar_sync288(4);
            const uint32_t n_empty = __shfl_sync(0xffffffffu, f_empty, n), n_due = __shfl_sync(0xffffffffu, f_due, n);
            if (n_empty) mbar_wait0(n_empty);
            #pragma unroll 1
            for (uint32_t k = 0; k < SPIN_LIMIT && (int32_t)(gtime32() - n_due) < 0; k++) {}
            if (n == i && (i != 4 || cta < 112)) {
                mbar_expect_tx(f_bar, f_bytes);
                if (f_bulk) bulk_g2s(f_dst, f_ptr, SLOT, f_bar);
                else tma2d(f_dst, (const CUtensorMap*)f_ptr, f_c0, f_c1, f_bar);
                if (i == 4) tma2d(f_dst + 8192, (const CUtensorMap*)f_ptr, f_c0, 256, f_bar);
            }
        }
        return;
    }

    if (warp == 9) {
        const uint32_t cnt0 = ld_rlx(scr->cnt + hkv * 32);
        const uint4 pz = make_uint4(POISON, POISON, POISON, POISON);
        st_rlx4(scr->q + (lane >> 2) * 2048 + cta * 16 + (lane & 3) * 4, pz);
        if (lane < 16 && cta < 112) st_rlx4(scr->h + cta * 64 + lane * 4, pz);
        if (lane < 2) st_rlx4(scr->st + cta * 8 + lane * 4, pz);
        st_rlx4(scr->o + cta * 256 + lane * 4, pz);
        st_rlx4(scr->o + cta * 256 + 128 + lane * 4, pz);
        if (lane < 16) st_rlx4(reinterpret_cast<uint32_t*>(scr->acc) + cta * 64 + lane * 4, make_uint4(0u, 0u, 0u, 0u));
        __syncwarp();
        bar_arrive288(3);
        const uint32_t target = (cnt0 & ~15u) + 16u;
        if (lane == 0) {
            TRACE(11);
            asm volatile("fence.acq_rel.gpu;" ::: "memory");
            TRACE(12);
            asm volatile("red.relaxed.gpu.global.add.u32 [%0], 1;" :: "l"(scr->cnt + hkv * 32) : "memory");
            #pragma unroll 1
            for (uint32_t n = 0; (int32_t)(ld_acq(scr->cnt + hkv * 32) - target) < 0; n++) if (n > SPIN_LIMIT) __trap();
            TRACE(3);
        }
        __syncwarp();
        bar_sync288(5);
        mbar_wait0(bar_emptyA);
        if (pace.qdelay) __nanosleep(pace.qdelay);
        {
            const uint32_t* pq = scr->q + bb * 2048 + hkv * 256 + lane * 4;
            uint4 v0, v1;
            #pragma unroll 1
            for (uint32_t n = 0; ; n++) {
                v0 = ld_rlx4(pq); v1 = ld_rlx4(pq + 128);
                if (!__any_sync(0xffffffffu, has_poison(v0) || has_poison(v1))) break;
                if (n > SPIN_LIMIT) __trap();
            }
            const uint32_t a = sb + SM_Q + (lane >> 4) * 272 + (lane & 15) * 16;
            sts128(a, v0); sts128(a + 544, v1);
            __syncwarp();
            if (lane == 0) { mbar_arrive(bar_q); TRACE(23); }
        }
        #pragma unroll 1
        for (uint32_t n = 0; __any_sync(0xffffffffu, (int32_t)(ld_acq(scr->cnt + (lane & 7) * 32) - target) < 0); n++)
            if (n > SPIN_LIMIT) __trap();
        if (lane == 0) TRACE(20);
        mbar_wait0(bar_full + 12 * 8);
        {
            const uint32_t* p3 = lane < 16 ? scr->h + kg * 448 + 384 + lane * 4 : scr->st + (cta ^ 1) * 8 + (lane & 1) * 4;
            uint4 v[4];
            #pragma unroll 1
            for (uint32_t n = 0; ; n++) {
                #pragma unroll
                for (int i = 0; i < 3; i++) v[i] = ld_rlx4(scr->h + kg * 448 + i * 128 + lane * 4);
                v[3] = ld_rlx4(p3);
                if (!__any_sync(0xffffffffu, has_poison(v[0]) || has_poison(v[1]) || has_poison(v[2]) || has_poison(v[3]))) break;
                if (n > SPIN_LIMIT) __trap();
            }
            #pragma unroll
            for (int i = 0; i < 3; i++) sts128(sb + SM_H + i * 512 + lane * 16, v[i]);
            if (lane < 18) sts128(lane < 16 ? sb + SM_H + 1536 + lane * 16 : sb + SM_ST + (lane & 1) * 16, v[3]);
        }
        __syncwarp();
        if (lane == 0) { mbar_arrive(bar_st); TRACE(32); }
        return;
    }

    const uint4 xa = *reinterpret_cast<const uint4*>(x + warp * 512 + lane * 8);
    const uint4 xb = *reinterpret_cast<const uint4*>(x + warp * 512 + 256 + lane * 8);
    if (lane == 0) {
        #pragma unroll 1
        for (int j = 5 + warp; j < NBAR; j += 8) mbar_init(bar_full + j * 8, j == NBAR - 1 ? 4 : 1);
        mbar_fence_init();
    }
    __syncwarp();
    bar_arrive288(4);
    bar_arrive288(5);
    if (tid == 0) TRACE(13);
    {
        float xv[16];
        const uint32_t xw[8] = {xa.x, xa.y, xa.z, xa.w, xb.x, xb.y, xb.z, xb.w};
        #pragma unroll
        for (int i = 0; i < 8; i++) { xv[2 * i] = bf_lo(xw[i]); xv[2 * i + 1] = bf_hi(xw[i]); }
        float s = 0.f;
        #pragma unroll
        for (int i = 0; i < 16; i++) s += xv[i];
        #pragma unroll
        for (int o = 16; o; o >>= 1) s += __shfl_xor_sync(0xffffffffu, s, o);
        const float mean = s * (1.f / 512.f);
        if (tid == 0) TRACE(14);
        float q = 0.f;
        #pragma unroll
        for (int i = 0; i < 16; i++) { const float d = xv[i] - mean; q += d * d; }
        #pragma unroll
        for (int o = 16; o; o >>= 1) q += __shfl_xor_sync(0xffffffffu, q, o);
        const float mb = bf16r(mean);
        const float den = bf16r(sqrt_approx(bf16r(bf16r(q * (1.f / 512.f)) + 1e-5f)));
        uint32_t o[8];
        #pragma unroll
        for (int i = 0; i < 8; i++)
            o[i] = pack_bf16(__fdividef(bf16r(xv[2 * i] - mb), den), __fdividef(bf16r(xv[2 * i + 1] - mb), den));
        sts128(sb + SM_XN + warp * 1040 + lane * 16, make_uint4(o[0], o[1], o[2], o[3]));
        sts128(sb + SM_XN + warp * 1040 + 512 + lane * 16, make_uint4(o[4], o[5], o[6], o[7]));
    }
    if (tid == 0) TRACE(15);
    bar_sync288(2);
    bar_ln_done();
    if (tid == 0) TRACE(0);

    {
        uint32_t xf[4][2];
        #pragma unroll
        for (int s = 0; s < 4; s++) {
            const uint32_t a = sb + SM_XN + g * 1040 + (warp * 64 + s * 16 + 2 * t) * 2;
            xf[s][0] = lds32(a); xf[s][1] = lds32(a + 16);
        }
        float acc[3][4] = {};
        const int mi = lane >> 3, rr = lane & 7;
        const int krow = (warp & 3) * 64 + (mi >> 1) * 8 + rr;
        mbar_wait0(bar_full + (2 + (warp >> 2)) * 8);
        if (tid == 0) TRACE(16);
        if (tid == 128) TRACE(17);
        #pragma unroll
        for (int s = 0; s < 4; s++) {
            const int r = krow + s * 16;
            #pragma unroll
            for (int mt = 0; mt < 2; mt++) {
                uint32_t a[4];
                ldsm_x4_t(a, sb + (2 + (warp >> 2)) * SLOT + r * 64 + (((2 * mt + (mi & 1)) ^ ((r >> 1) & 3)) << 4));
                mma16816(acc[mt], a[0], a[1], a[2], a[3], xf[s][0], xf[s][1]);
            }
        }
        if (cta < 112) {
            mbar_wait0(bar_full + 4 * 8);
            if (tid == 0) TRACE(18);
            #pragma unroll
            for (int s = 0; s < 4; s++) {
                const int r = (warp >> 2) * 256 + krow + s * 16;
                uint32_t a[4];
                ldsm_x4_t(a, sb + 4 * SLOT + r * 32 + (((mi & 1) ^ ((r >> 2) & 1)) << 4));
                mma16816(acc[2], a[0], a[1], a[2], a[3], xf[s][0], xf[s][1]);
            }
        }
        #pragma unroll
        for (int mt = 0; mt < 3; mt++)
            sts128(sb + SM_RED + (warp * 3 + mt) * 512 + lane * 16,
                   make_uint4(__float_as_uint(acc[mt][0]), __float_as_uint(acc[mt][1]), __float_as_uint(acc[mt][2]), __float_as_uint(acc[mt][3])));
    }
    bar_consumers();
    if (tid == 0) { TRACE(1); mbar_arrive(bar_emptyA); }
    if (tid < 192) {
        const int tile = tid < 128 ? ((tid >> 3) & 1) : 2;
        const int b = tid < 128 ? (tid >> 4) : ((tid - 128) >> 3);
        const int j = tid & 7;
        const uint32_t a = sb + SM_RED + tile * 512 + (4 * ((2 * j) & 7) + (b >> 1)) * 16 + (2 * (j >> 2) + (b & 1)) * 4;
        float v0 = 0.f, v1 = 0.f;
        #pragma unroll
        for (int w = 0; w < 8; w++) { v0 += lds32f(a + w * 1536); v1 += lds32f(a + w * 1536 + 64); }
        if (tid < 128) {
            st_rlx(scr->q + b * 2048 + cta * 16 + (tid & 15), unpoison(pack_bf16(v0, v1)));
        } else if (cta < 112) {
            v0 = bf16r(v0); v1 = bf16r(v1);
            v0 = __fdividef(v0, 1.f + __expf(-v0));
            v1 = __fdividef(v1, 1.f + __expf(-v1));
            st_rlx(scr->h + cta * 64 + b * 8 + 2 * (j & 3) + (j >> 2), unpoison(pack_bf16(v0, v1)));
        }
    }
    if (tid == 0) TRACE(2);

    float sc[4][4] = {};
    {
        uint4 qf[4];
        mbar_wait0(bar_q);
        #pragma unroll
        for (int j = 0; j < 4; j++) qf[j] = lds128(sb + SM_Q + (g & 3) * 272 + (4 * (j ^ (g >> 2)) + t) * 16);
        const int fill = warp < 2 ? warp : warp + 3;
        mbar_wait0(bar_full + fill * 8);
        if (tid == 0 && qf[3].w != 0x12345) TRACE(19);
        const uint32_t kb = sb + fill * SLOT + g * 256 + t * 16;
        #pragma unroll
        for (int j = 0; j < 4; j++) {
            #pragma unroll
            for (int mt = 0; mt < 4; mt++) {
                const uint32_t a = kb + mt * 4096 + ((j ^ (g & 1)) << 6);
                const uint4 lo = lds128(a), hi = lds128(a + 2048);
                mma16816(sc[mt], lo.x, hi.x, lo.y, hi.y, qf[j].x, qf[j].y);
                mma16816(sc[mt], lo.z, hi.z, lo.w, hi.w, qf[j].z, qf[j].w);
            }
        }
        __syncwarp();
        if (lane == 0 && warp < 7) mbar_arrive(bar_emptyK + warp * 8);
    }
    if (tid == 0) TRACE(4);
    if (tid == 224) TRACE(5);
    const bool valid = (t >> 1) == (g & 1);
    const int h0 = 2 * (t & 1);
    {
        float m0 = -INFINITY, m1 = -INFINITY;
        #pragma unroll
        for (int mt = 0; mt < 4; mt++) {
            #pragma unroll
            for (int i = 0; i < 4; i++) sc[mt][i] = bf16r(bf16r(sc[mt][i]) * 0.08838834764831845f);
            m0 = fmaxf(m0, fmaxf(sc[mt][0], sc[mt][2]));
            m1 = fmaxf(m1, fmaxf(sc[mt][1], sc[mt][3]));
        }
        if (!valid) { m0 = -INFINITY; m1 = -INFINITY; }
        #pragma unroll
        for (int o = 2; o <= 16; o <<= 1) {
            m0 = fmaxf(m0, __shfl_xor_sync(0xffffffffu, m0, o));
            m1 = fmaxf(m1, __shfl_xor_sync(0xffffffffu, m1, o));
        }
        if (lane < 2) { sts32f(sb + SM_WMAX + warp * 16 + h0 * 4, m0); sts32f(sb + SM_WMAX + warp * 16 + h0 * 4 + 4, m1); }
    }
    bar_consumers();
    if (tid == 0) TRACE(21);
    float mloc0 = -INFINITY, mloc1 = -INFINITY;
    {
        #pragma unroll
        for (int w = 0; w < 8; w++) {
            mloc0 = fmaxf(mloc0, lds32f(sb + SM_WMAX + w * 16 + h0 * 4));
            mloc1 = fmaxf(mloc1, lds32f(sb + SM_WMAX + w * 16 + h0 * 4 + 4));
        }
        const float L2E = 1.4426950408889634f;
        float l0 = 0.f, l1 = 0.f;
        const uint32_t pa = sb + SM_P + (h0 * 260 + warp * 32 + (g & 3) * 8 + (g >> 2)) * 4;
        #pragma unroll
        for (int mt = 0; mt < 4; mt++) {
            const float p0 = ex2((sc[mt][0] - mloc0) * L2E), p2 = ex2((sc[mt][2] - mloc0) * L2E);
            const float p1 = ex2((sc[mt][1] - mloc1) * L2E), p3 = ex2((sc[mt][3] - mloc1) * L2E);
            l0 += p0 + p2; l1 += p1 + p3;
            if (valid) { sts32(pa + mt * 8, pack_bf16(p0, p2)); sts32(pa + 1040 + mt * 8, pack_bf16(p1, p3)); }
        }
        if (!valid) { l0 = 0.f; l1 = 0.f; }
        #pragma unroll
        for (int o = 2; o <= 16; o <<= 1) {
            l0 += __shfl_xor_sync(0xffffffffu, l0, o);
            l1 += __shfl_xor_sync(0xffffffffu, l1, o);
        }
        if (lane < 2) { sts32f(sb + SM_WSUM + warp * 16 + h0 * 4, l0); sts32f(sb + SM_WSUM + warp * 16 + h0 * 4 + 4, l1); }
    }
    if (tid == 0) TRACE(22);
    bar_consumers();
    if (tid == 0) TRACE(6);
    float lloc0 = 0.f, lloc1 = 0.f;
    #pragma unroll
    for (int w = 0; w < 8; w++) {
        lloc0 += lds32f(sb + SM_WSUM + w * 16 + h0 * 4);
        lloc1 += lds32f(sb + SM_WSUM + w * 16 + h0 * 4 + 4);
    }
    if (tid < 2) {
        st_rlx(scr->st + cta * 8 + h0, unpoison(__float_as_uint(mloc0)));
        st_rlx(scr->st + cta * 8 + h0 + 1, unpoison(__float_as_uint(mloc1)));
        st_rlx(scr->st + cta * 8 + 4 + h0, unpoison(__float_as_uint(lloc0)));
        st_rlx(scr->st + cta * 8 + 4 + h0 + 1, unpoison(__float_as_uint(lloc1)));
    }

    float oa[4][4] = {};
    uint32_t* pub = scr->o + cta * 256 + h0 * 64 + warp * 8 + g;
    keep64(pub);
    float scale0 = 0.f, scale1 = 0.f;
    {
        const int mi = lane >> 3, rr = lane & 7;
        const int key = (rr >> 1) + 4 * (mi >> 1) + 8 * (rr & 1);
        const int rowp = 2 * key + (warp >> 2);
        const uint32_t voff = rowp * 128 + (((2 * (warp & 3) + (mi & 1)) ^ (rowp & 7)) << 4);
        #pragma unroll 1
        for (int vc = 0; vc < 8; vc++) {
            uint4 p0 = make_uint4(0u, 0u, 0u, 0u), p1 = p0;
            if (g < 4) {
                const uint32_t a = sb + SM_P + (g * 260 + vc * 32 + t * 8) * 4;
                p0 = lds128(a); p1 = lds128(a + 16);
            }
            if (vc == 7) {
                mbar_wait0(bar_st);
                const float L2E = 1.4426950408889634f;
                const float mo0 = lds32f(sb + SM_ST + h0 * 4), mo1 = lds32f(sb + SM_ST + h0 * 4 + 4);
                const float mg0 = fmaxf(mloc0, mo0), mg1 = fmaxf(mloc1, mo1);
                const float e0 = ex2((mloc0 - mg0) * L2E), e1 = ex2((mloc1 - mg1) * L2E);
                scale0 = __fdividef(e0, lloc0 * e0 + lds32f(sb + SM_ST + 16 + h0 * 4) * ex2((mo0 - mg0) * L2E));
                scale1 = __fdividef(e1, lloc1 * e1 + lds32f(sb + SM_ST + 20 + h0 * 4) * ex2((mo1 - mg1) * L2E));
            }
            const int fill = 11 + vc, slot = vc == 0 ? 11 : (vc < 4 ? vc + 1 : (vc < 6 ? vc - 4 : vc - 1));
            mbar_wait0(bar_full + fill * 8);
            if (tid == 0) TRACE(24 + vc);
            const uint32_t vb = sb + slot * SLOT + voff;
            uint32_t a0[4], a1[4], a2[4], a3[4];
            ldsm_x4_t(a0, vb); ldsm_x4_t(a1, vb + 4096); ldsm_x4_t(a2, vb + 8192); ldsm_x4_t(a3, vb + 12288);
            mma16816(oa[0], a0[0], a0[1], a0[2], a0[3], p0.x, p0.y);
            mma16816(oa[1], a1[0], a1[1], a1[2], a1[3], p0.z, p0.w);
            mma16816(oa[2], a2[0], a2[1], a2[2], a2[3], p1.x, p1.y);
            mma16816(oa[3], a3[0], a3[1], a3[2], a3[3], p1.z, p1.w);
        }
        if (tid == 0) TRACE(7);
        float os[4];
        #pragma unroll
        for (int i = 0; i < 4; i++) os[i] = (oa[0][i] + oa[1][i]) + (oa[2][i] + oa[3][i]);
        const uint32_t lo = pack_bf16(os[0] * scale0, os[1] * scale1);
        const uint32_t hi = pack_bf16(os[2] * scale0, os[3] * scale1);
        const bool odd = g & 1;
        const uint32_t y = __shfl_xor_sync(0xffffffffu, odd ? lo : hi, 4);
        const uint32_t first = odd ? y : lo, second = odd ? hi : y;
        if (t < 2) {
            st_rlx(pub, unpoison(__byte_perm(first, second, 0x5410)));
            st_rlx(pub + 64, unpoison(__byte_perm(first, second, 0x7632)));
        }
        if (tid == 0) TRACE(49);
    }

    if (warp >= 4) {
        const uint32_t* po = scr->o + (hkv * 16 + (warp - 4) * 4) * 256 + (kg & 1) * 128 + lane * 4;
        uint32_t so = sb + SM_O + (warp - 4) * 1152 + (lane >> 2) * 64 + (lane & 1) * 32 + (lane & 2) * 4;
        keep64(po); keep32(so);
        mbar_wait0(bar_full + pace.opoll * 8);
        if (pace.rot) { const uint32_t c0 = clk32(); while (clk32() - c0 < (uint32_t)pace.rot) {} }
        if (tid == 128) TRACE(34);
        uint4 v[4];
        #pragma unroll
        for (int i = 0; i < 4; i++) v[i] = ld_rlx4(po + i * 256);
        #pragma unroll 1
        for (uint32_t n = 0; ; n++) {
            bool bad[4];
            #pragma unroll
            for (int i = 0; i < 4; i++) bad[i] = __any_sync(0xffffffffu, has_poison(v[i]));
            if (!(bad[0] || bad[1] || bad[2] || bad[3])) break;
            #pragma unroll
            for (int i = 0; i < 4; i++) if (bad[i]) v[i] = ld_rlx4(po + i * 256);
            if (n > SPIN_LIMIT) __trap();
        }
        #pragma unroll
        for (int i = 0; i < 2; i++) {
            sts64(so + i * 576, hadd2_bf16(v[2 * i].x, v[2 * i + 1].x), hadd2_bf16(v[2 * i].y, v[2 * i + 1].y));
            sts64(so + i * 576 + 16, hadd2_bf16(v[2 * i].z, v[2 * i + 1].z), hadd2_bf16(v[2 * i].w, v[2 * i + 1].w));
        }
        __syncwarp();
        if (lane == 0) mbar_arrive(bar_o);
        if (lane == 0) TRACE(40 + warp);
        return;
    }
    {
        float acc[8][4] = {};
        uint32_t wa[4][4][4];
        const int mi = lane >> 3, rr = lane & 7;
        uint32_t wb = sb + 8 * SLOT + ((mi >> 1) * 8 + rr) * 128 + (((2 * warp + (mi & 1)) ^ rr) << 4);
        uint32_t so = sb + SM_O + g * 576 + t * 16;
        const int ocol = 64 * cg + 16 * warp + g;
        float* pacc = scr->acc + (cg * 4 + warp) * 256 + lane * 4;
        __nv_bfloat16* pout = out + 2 * t * 512 + ocol;
        keep32(wb); keep32(so); keep64(pacc); keep64(pout);
        const __nv_bfloat16* px = x + 2 * t * 512 + ocol;
        const __nv_bfloat16 b0 = px[0], b1 = px[512], b2 = px[8], b3 = px[520];
        mbar_wait0(bar_full + 19 * 8);
        if (tid == 0) TRACE(8);
        #pragma unroll
        for (int i = 0; i < 7; i++) {
            uint32_t a[4];
            ldsm_x4_t(a, wb - SLOT + i * 2048);
            const uint32_t ha = sb + SM_H + i * 256 + lane * 8;
            mma16816(acc[i], a[0], a[1], a[2], a[3], lds32(ha), lds32(ha + 4));
        }
        float x0 = __bfloat162float(b0), x1 = __bfloat162float(b1), x2 = __bfloat162float(b2), x3 = __bfloat162float(b3);
        keepf(x0); keepf(x1); keepf(x2); keepf(x3);
        #pragma unroll
        for (int pc = 0; pc < 3; pc++) {
            mbar_wait0(bar_full + (20 + pc) * 8);
            #pragma unroll
            for (int k = 0; k < 4; k++) ldsm_x4_t(wa[pc][k], wb + pc * 8192 + k * 2048);
        }
        bool o_first;
        #pragma unroll 1
        for (uint32_t n = 0; ; n++) {
            o_first = mbar_test0(bar_o);
            if (o_first || mbar_test0(bar_full + 23 * 8)) break;
            if (n > SPIN_LIMIT * 16) __trap();
        }
        uint4 of[8];
        if (!o_first) {
            #pragma unroll
            for (int k = 0; k < 4; k++) ldsm_x4_t(wa[3][k], wb + 24576 + k * 2048);
            mbar_wait0(bar_o);
        }
        if (tid == 0) { TRACE(9); TRACE(48); }
        #pragma unroll
        for (int i = 0; i < 8; i++) of[i] = lds128(so + i * 64);
        #pragma unroll
        for (int pc = 0; pc < 3; pc++) {
            #pragma unroll
            for (int k = 0; k < 4; k++) {
                const uint4& u = of[2 * pc + (k >> 1)];
                mma16816(acc[(pc & 1) * 4 + k], wa[pc][k][0], wa[pc][k][1], wa[pc][k][2], wa[pc][k][3], k & 1 ? u.z : u.x, k & 1 ? u.w : u.y);
            }
        }
        if (o_first) {
            #pragma unroll
            for (int i = 0; i < 4; i++) acc[0][i] = (acc[0][i] + acc[1][i]) + (acc[2][i] + acc[3][i]);
            mbar_wait0(bar_full + 23 * 8);
            #pragma unroll
            for (int k = 0; k < 4; k++) ldsm_x4_t(wa[3][k], wb + 24576 + k * 2048);
        }
        #pragma unroll
        for (int k = 0; k < 4; k++) {
            const uint4& u = of[6 + (k >> 1)];
            mma16816(acc[4 + k], wa[3][k][0], wa[3][k][1], wa[3][k][2], wa[3][k][3], k & 1 ? u.z : u.x, k & 1 ? u.w : u.y);
        }
        if (!o_first) {
            #pragma unroll
            for (int i = 0; i < 4; i++) acc[0][i] = (acc[0][i] + acc[1][i]) + (acc[2][i] + acc[3][i]);
        }
        float r[4];
        #pragma unroll
        for (int i = 0; i < 4; i++) r[i] = (acc[4][i] + acc[5][i]) + (acc[6][i] + acc[7][i]) + acc[0][i];
        float4 o0, o1;
        asm volatile("atom.relaxed.gpu.global.add.v4.f32 {%0,%1,%2,%3}, [%4], {%5,%6,%7,%8};"
                     : "=f"(o0.x), "=f"(o0.y), "=f"(o0.z), "=f"(o0.w) : "l"(pacc), "f"(r[0]), "f"(r[1]), "f"(1.f), "f"(0.f) : "memory");
        asm volatile("atom.relaxed.gpu.global.add.v4.f32 {%0,%1,%2,%3}, [%4], {%5,%6,%7,%8};"
                     : "=f"(o1.x), "=f"(o1.y), "=f"(o1.z), "=f"(o1.w) : "l"(pacc + 128), "f"(r[2]), "f"(r[3]), "f"(1.f), "f"(0.f) : "memory");
        if (tid == 0) TRACE(10);
        r[0] += x0; r[1] += x1; r[2] += x2; r[3] += x3;
        if (o0.z == 15.f) {
            pout[0] = __float2bfloat16_rn(o0.x + r[0]);
            pout[512] = __float2bfloat16_rn(o0.y + r[1]);
        }
        if (o1.z == 15.f) {
            pout[8] = __float2bfloat16_rn(o1.x + r[2]);
            pout[520] = __float2bfloat16_rn(o1.y + r[3]);
        }
    }
}

typedef CUresult (*EncodeTiledFn)(CUtensorMap*, CUtensorMapDataType, cuuint32_t, void*, const cuuint64_t*, const cuuint64_t*,
                                  const cuuint32_t*, const cuuint32_t*, CUtensorMapInterleave, CUtensorMapSwizzle,
                                  CUtensorMapL2promotion, CUtensorMapFloatOOBfill);

void make_map(EncodeTiledFn enc, CUtensorMap* m, const void* base, uint64_t cols, uint64_t rows, uint32_t box_cols,
              uint32_t box_rows, CUtensorMapSwizzle sw) {
    cuuint64_t gd[2] = {cols, rows};
    cuuint64_t gs[1] = {cols * 2};
    cuuint32_t bd[2] = {box_cols, box_rows};
    cuuint32_t es[2] = {1, 1};
    enc(m, CU_TENSOR_MAP_DATA_TYPE_BFLOAT16, 2, const_cast<void*>(base), gd, gs, bd, es, CU_TENSOR_MAP_INTERLEAVE_NONE, sw,
        CU_TENSOR_MAP_L2_PROMOTION_L2_256B, CU_TENSOR_MAP_FLOAT_OOB_FILL_NONE);
}

}

extern "C" void kernel_launch(void* const* d_in, const int* in_sizes, int n_in, void* d_out, int out_size) {
    (void)in_sizes; (void)n_in; (void)out_size;
    static EncodeTiledFn enc = nullptr;
    static Scratch* scr = nullptr;
    if (!enc) {
        cudaGetSymbolAddress((void**)&scr, g_scratch);
        void* fn = nullptr;
        cudaDriverEntryPointQueryResult qr;
        cudaGetDriverEntryPoint("cuTensorMapEncodeTiled", &fn, cudaEnableDefault, &qr);
        enc = (EncodeTiledFn)fn;
        cudaFuncSetAttribute(fused_decode_kernel, cudaFuncAttributeMaxDynamicSharedMemorySize, SMEM_BYTES);
    }
    TMaps tm;
    make_map(enc, &tm.wq, d_in[3], 4096, 512, 32, 256, CU_TENSOR_MAP_SWIZZLE_64B);
    make_map(enc, &tm.w1, d_in[6], 1792, 512, 16, 256, CU_TENSOR_MAP_SWIZZLE_32B);
    make_map(enc, &tm.v, d_in[2], 64, 8ull * 8 * 4096 * 2, 64, 128, CU_TENSOR_MAP_SWIZZLE_128B);
    make_map(enc, &tm.wo, d_in[4], 512, 4096, 64, 64, CU_TENSOR_MAP_SWIZZLE_128B);
    make_map(enc, &tm.w2, d_in[7], 512, 1792, 64, 112, CU_TENSOR_MAP_SWIZZLE_128B);
    fused_decode_kernel<<<NCTA, NTHREADS, SMEM_BYTES, cudaStreamPerThread>>>(
        (const __nv_bfloat16*)d_in[1], (const __nv_bfloat16*)d_in[0], (__nv_bfloat16*)d_out, scr,
        tm);
}
```

```cpp
#include <cuda_runtime.h>
#include <cuda_bf16.h>
#include <cuda.h>
#include <stdint.h>

namespace {

constexpr int NCTA = 128;
constexpr int NTHREADS = 320;
constexpr int SLOT = 16384;
constexpr int NSLOT = 12;
constexpr int NFILL = 24;
constexpr uint32_t POISON = 0xFFFFFFFFu;
constexpr uint32_t SPIN_LIMIT = 1u << 21;

constexpr int PACE_T0 = 500, PACE_TAU = 650, PACE_TAIL_FROM = 16, PACE_TAIL_EXTRA = 70;

constexpr int SM_XN = NSLOT * SLOT;
constexpr int SM_RED = SM_XN + 8 * 1040;
constexpr int SM_P = SM_RED + 8 * 3 * 512;
constexpr int SM_WMAX = SM_P + 4 * 260 * 4;
constexpr int SM_WSUM = SM_WMAX + 128;
constexpr int SM_ST = SM_WSUM + 128;
constexpr int SM_Q = SM_ST + 32;
constexpr int SM_H = SM_Q + 4 * 272;
constexpr int SM_O = SM_RED;
constexpr int SM_BAR = SM_H + 7 * 256;
constexpr int NBAR = NFILL + 7 + 4;
constexpr int SM_TOTAL = SM_BAR + NBAR * 8;
constexpr int SMEM_BYTES = SM_TOTAL + 1024;

struct TMaps { CUtensorMap wq, w1, v, wo, w2; };

struct Scratch {
    float acc[8 * 4 * 2 * 128];
    uint32_t o[NCTA * 256];
    uint32_t q[8 * 2048];
    uint32_t h[112 * 64];
    uint32_t st[NCTA * 8];
    uint32_t cnt[8 * 32];
};
__device__ __align__(128) Scratch g_scratch;

__device__ __forceinline__ uint32_t clk32() { uint32_t c; asm volatile("mov.u32 %0, %clock;" : "=r"(c)); return c; }
__device__ __forceinline__ uint32_t gtime32() { uint32_t c; asm volatile("mov.u32 %0, %globaltimer_lo;" : "=r"(c)); return c; }
__device__ __forceinline__ uint32_t smem_u32(const void* p) { return (uint32_t)__cvta_generic_to_shared(p); }

__device__ __forceinline__ void mbar_init(uint32_t bar, uint32_t cnt) {
    asm volatile("mbarrier.init.shared::cta.b64 [%0], %1;" :: "r"(bar), "r"(cnt) : "memory");
}
__device__ __forceinline__ void mbar_fence_init() { asm volatile("fence.mbarrier_init.release.cluster;" ::: "memory"); }
__device__ __forceinline__ void mbar_expect_tx(uint32_t bar, uint32_t bytes) {
    asm volatile("mbarrier.arrive.expect_tx.shared::cta.b64 _, [%0], %1;" :: "r"(bar), "r"(bytes) : "memory");
}
__device__ __forceinline__ void mbar_arrive(uint32_t bar) {
    asm volatile("mbarrier.arrive.shared::cta.b64 _, [%0];" :: "r"(bar) : "memory");
}
__device__ __forceinline__ void mbar_wait0(uint32_t bar) {
    #pragma unroll 1
    for (uint32_t i = 0; i < SPIN_LIMIT; i++) {
        uint32_t ok;
        asm volatile("{\n.reg .pred p;\nmbarrier.try_wait.parity.shared::cta.b64 p, [%1], 0;\nselp.u32 %0, 1, 0, p;\n}"
                     : "=r"(ok) : "r"(bar) : "memory");
        if (ok) return;
    }
    __trap();
}
constexpr uint64_t EVICT_FIRST = 0x12F0000000000000ull;
__device__ __forceinline__ bool mbar_test0(uint32_t bar) {
    uint32_t ok;
    asm volatile("{\n.reg .pred p;\nmbarrier.test_wait.parity.shared::cta.b64 p, [%1], 0;\nselp.u32 %0, 1, 0, p;\n}"
                 : "=r"(ok) : "r"(bar) : "memory");
    return ok;
}
__device__ __forceinline__ void bulk_g2s(uint32_t dst, const void* src, uint32_t bytes, uint32_t bar) {
    asm volatile("cp.async.bulk.shared::cluster.global.mbarrier::complete_tx::bytes.L2::cache_hint [%0], [%1], %2, [%3], %4;"
                 :: "r"(dst), "l"(src), "r"(bytes), "r"(bar), "l"(EVICT_FIRST) : "memory");
}
__device__ __forceinline__ void tma2d(uint32_t dst, const CUtensorMap* tm, int c0, int c1, uint32_t bar) {
    asm volatile("cp.async.bulk.tensor.2d.shared::cluster.global.mbarrier::complete_tx::bytes.L2::cache_hint [%0], [%1, {%3, %4}], [%2], %5;"
                 :: "r"(dst), "l"(tm), "r"(bar), "r"(c0), "r"(c1), "l"(EVICT_FIRST) : "memory");
}
__device__ __forceinline__ void bar_consumers() { asm volatile("bar.sync 1, 256;" ::: "memory"); }
__device__ __forceinline__ void bar_sync288(int id) { asm volatile("bar.sync %0, 288;" :: "r"(id) : "memory"); }
__device__ __forceinline__ void bar_arrive288(int id) { asm volatile("bar.arrive %0, 288;" :: "r"(id) : "memory"); }
template <typename T> __device__ __forceinline__ void keep64(T*& p) { asm volatile("" : "+l"(p)); }
__device__ __forceinline__ void keep32(uint32_t& v) { asm volatile("" : "+r"(v)); }
__device__ __forceinline__ void keepf(float& v) { asm volatile("" : "+f"(v)); }
__device__ __forceinline__ uint32_t hadd2_bf16(uint32_t a, uint32_t b) {
    uint32_t r; asm("add.rn.bf16x2 %0, %1, %2;" : "=r"(r) : "r"(a), "r"(b)); return r;
}

__device__ __forceinline__ uint4 lds128(uint32_t a) {
    uint4 v; asm volatile("ld.shared.v4.u32 {%0,%1,%2,%3}, [%4];" : "=r"(v.x), "=r"(v.y), "=r"(v.z), "=r"(v.w) : "r"(a)); return v;
}
__device__ __forceinline__ uint32_t lds32(uint32_t a) { uint32_t v; asm volatile("ld.shared.u32 %0, [%1];" : "=r"(v) : "r"(a)); return v; }
__device__ __forceinline__ float lds32f(uint32_t a) { float v; asm volatile("ld.shared.f32 %0, [%1];" : "=f"(v) : "r"(a)); return v; }
__device__ __forceinline__ void sts32(uint32_t a, uint32_t v) { asm volatile("st.shared.u32 [%0], %1;" :: "r"(a), "r"(v) : "memory"); }
__device__ __forceinline__ void sts32f(uint32_t a, float v) { asm volatile("st.shared.f32 [%0], %1;" :: "r"(a), "f"(v) : "memory"); }
__device__ __forceinline__ void sts64(uint32_t a, uint32_t x, uint32_t y) {
    asm volatile("st.shared.v2.u32 [%0], {%1,%2};" :: "r"(a), "r"(x), "r"(y) : "memory");
}
__device__ __forceinline__ void sts128(uint32_t a, uint4 v) {
    asm volatile("st.shared.v4.u32 [%0], {%1,%2,%3,%4};" :: "r"(a), "r"(v.x), "r"(v.y), "r"(v.z), "r"(v.w) : "memory");
}
__device__ __forceinline__ void ldsm_x4_t(uint32_t (&r)[4], uint32_t a) {
    asm volatile("ldmatrix.sync.aligned.m8n8.x4.trans.shared.b16 {%0,%1,%2,%3}, [%4];"
                 : "=r"(r[0]), "=r"(r[1]), "=r"(r[2]), "=r"(r[3]) : "r"(a));
}
__device__ __forceinline__ void mma16816(float (&c)[4], uint32_t a0, uint32_t a1, uint32_t a2, uint32_t a3, uint32_t b0, uint32_t b1) {
    asm volatile("mma.sync.aligned.m16n8k16.row.col.f32.bf16.bf16.f32 {%0,%1,%2,%3}, {%4,%5,%6,%7}, {%8,%9}, {%0,%1,%2,%3};"
                 : "+f"(c[0]), "+f"(c[1]), "+f"(c[2]), "+f"(c[3]) : "r"(a0), "r"(a1), "r"(a2), "r"(a3), "r"(b0), "r"(b1));
}

__device__ __forceinline__ uint32_t ld_rlx(const uint32_t* p) {
    uint32_t v; asm volatile("ld.relaxed.gpu.global.u32 %0, [%1];" : "=r"(v) : "l"(p) : "memory"); return v;
}
__device__ __forceinline__ uint32_t ld_acq(const uint32_t* p) {
    uint32_t v; asm volatile("ld.acquire.gpu.global.u32 %0, [%1];" : "=r"(v) : "l"(p) : "memory"); return v;
}
__device__ __forceinline__ uint4 ld_rlx4(const uint32_t* p) {
    uint4 v; asm volatile("ld.relaxed.gpu.global.v4.u32 {%0,%1,%2,%3}, [%4];" : "=r"(v.x), "=r"(v.y), "=r"(v.z), "=r"(v.w) : "l"(p) : "memory"); return v;
}
__device__ __forceinline__ void st_rlx(uint32_t* p, uint32_t v) {
    asm volatile("st.relaxed.gpu.global.u32 [%0], %1;" :: "l"(p), "r"(v) : "memory");
}
__device__ __forceinline__ void st_rlx4(uint32_t* p, uint4 v) {
    asm volatile("st.relaxed.gpu.global.v4.u32 [%0], {%1,%2,%3,%4};" :: "l"(p), "r"(v.x), "r"(v.y), "r"(v.z), "r"(v.w) : "memory");
}
__device__ __forceinline__ bool has_poison(const uint4& v) {
    return v.x == POISON || v.y == POISON || v.z == POISON || v.w == POISON;
}
__device__ __forceinline__ uint32_t unpoison(uint32_t w) { return w == POISON ? 0x7FFFFFFFu : w; }

__device__ __forceinline__ float sqrt_approx(float x) { float r; asm("sqrt.approx.f32 %0, %1;" : "=f"(r) : "f"(x)); return r; }
__device__ __forceinline__ float ex2(float x) { float r; asm("ex2.approx.ftz.f32 %0, %1;" : "=f"(r) : "f"(x)); return r; }
__device__ __forceinline__ float bf16r(float x) { return __bfloat162float(__float2bfloat16_rn(x)); }
__device__ __forceinline__ uint32_t pack_bf16(float lo, float hi) {
    uint32_t r; asm("cvt.rn.bf16x2.f32 %0, %1, %2;" : "=r"(r) : "f"(hi), "f"(lo)); return r;
}
__device__ __forceinline__ float bf_lo(uint32_t w) { return __uint_as_float(w << 16); }
__device__ __forceinline__ float bf_hi(uint32_t w) { return __uint_as_float(w & 0xFFFF0000u); }

__global__ void __launch_bounds__(NTHREADS, 1)
fused_decode_kernel(const __nv_bfloat16* __restrict__ kcache, const __nv_bfloat16* __restrict__ x,
                    __nv_bfloat16* __restrict__ out, Scratch* __restrict__ scr,
                    const __grid_constant__ TMaps tm)
{
    extern __shared__ uint8_t smem_raw[];
    const uint32_t sb = (smem_u32(smem_raw) + 1023u) & ~1023u;
    const int tid = threadIdx.x, warp = tid >> 5, lane = tid & 31;
    const int cta = blockIdx.x;
    const int hkv = cta >> 4, bb = (cta >> 1) & 7, half = cta & 1;
    const int kg = cta >> 3, cg = cta & 7;
    const int g = lane >> 2, t = lane & 3;
    const uint32_t bar_full = sb + SM_BAR, bar_emptyK = bar_full + NFILL * 8, bar_emptyA = bar_emptyK + 7 * 8;
    const uint32_t bar_q = bar_emptyA + 8, bar_st = bar_q + 8, bar_o = bar_st + 8;

    const int kvrow0 = (bb * 8 + hkv) * 4096 + 3072 + half * 512;
    uint32_t t_start = 0;
    if (tid == 288)
        asm volatile("cp.async.bulk.prefetch.L2.global.L2::cache_hint [%0], %1, %2;"
                     :: "l"(kcache + (size_t)kvrow0 * 128), "r"(2 * SLOT), "l"(EVICT_FIRST) : "memory");
    if (tid == 256) {
        mbar_init(bar_full, 1);
        mbar_init(bar_full + 8, 1);
        mbar_fence_init();
        mbar_expect_tx(bar_full, SLOT);
        bulk_g2s(sb, kcache + (size_t)kvrow0 * 128, SLOT, bar_full);
        mbar_expect_tx(bar_full + 8, SLOT);
        bulk_g2s(sb + SLOT, kcache + (size_t)(kvrow0 + 64) * 128, SLOT, bar_full + 8);
        t_start = gtime32();
    }

    if (warp == 8) {
        if (lane == 0) {
            asm volatile("prefetch.tensormap [%0];" :: "l"(&tm.wq));
            asm volatile("prefetch.tensormap [%0];" :: "l"(&tm.w1));
            asm volatile("prefetch.tensormap [%0];" :: "l"(&tm.v));
            asm volatile("prefetch.tensormap [%0];" :: "l"(&tm.wo));
            asm volatile("prefetch.tensormap [%0];" :: "l"(&tm.w2));
            mbar_init(bar_full + 16, 1); mbar_init(bar_full + 24, 1); mbar_init(bar_full + 32, 1);
            mbar_fence_init();
        }
        __syncwarp();
        bar_arrive288(2);
        const int i = lane;
        const int slot = i < NSLOT ? i : (i < 15 ? i - 10 : (i < 17 ? i - 15 : (i < 20 ? i - NSLOT : 8 + ((i - 20) >> 1))));
        const uint32_t f_empty = i < NSLOT ? 0u : (i < 15 ? bar_emptyA : bar_emptyK + (slot < 2 ? slot : slot - 3) * 8);
        const uint32_t f_bar = bar_full + i * 8;
        const uint32_t f_dst = sb + slot * SLOT + (i >= 20 ? (i & 1) * 8192 : 0);
        const uint32_t f_bytes = i >= 20 ? SLOT / 2 : (i == 19 ? 112 * 128 : SLOT);
        const bool f_bulk = i >= 5 && i <= 10;
        const void* f_ptr = i <= 3 ? (const void*)&tm.wq : i == 4 ? (const void*)&tm.w1
                          : f_bulk ? (const void*)(kcache + (size_t)(kvrow0 + ((i - 3) & 7) * 64) * 128)
                          : i <= 18 ? (const void*)&tm.v : i == 19 ? (const void*)&tm.w2 : (const void*)&tm.wo;
        const int f_c0 = i <= 3 ? cta * 32 : i == 4 ? cta * 16 : i <= 18 ? 0 : cg * 64;
        const int f_c1 = i <= 3 ? (i - 2) * 256 : i == 4 ? 0 : i <= 18 ? (kvrow0 + ((i - 11) & 7) * 64) * 2
                       : i == 19 ? kg * 112 : kg * 256 + (i - 20) * 64;
        const int phase = (cta * PACE_TAU) >> 7;
        uint32_t f_due = PACE_T0 + (i <= 19
            ? phase + (i - 2) * PACE_TAU + max(i - PACE_TAIL_FROM, 0) * PACE_TAIL_EXTRA - (i > 4 ? PACE_TAU >> 3 : 0)
            : (phase >> 1) + (((18 * 8 - 2 + (i - 20) * 4) * PACE_TAU) >> 3)
              + ((((20 - PACE_TAIL_FROM) * 2 + (i - 20)) * PACE_TAIL_EXTRA) >> 1));
        f_due += __shfl_sync(0xffffffffu, t_start, 0);
        #pragma unroll 1
        for (int n = 2; n < NFILL; n++) {
            if (n == 5) bar_sync288(4);
            const uint32_t n_empty = __shfl_sync(0xffffffffu, f_empty, n), n_due = __shfl_sync(0xffffffffu, f_due, n);
            if (n_empty) mbar_wait0(n_empty);
            #pragma unroll 1
            for (uint32_t k = 0; k < SPIN_LIMIT && (int32_t)(gtime32() - n_due) < 0; k++) {}
            if (n == i && (i != 4 || cta < 112)) {
                mbar_expect_tx(f_bar, f_bytes);
                if (f_bulk) bulk_g2s(f_dst, f_ptr, SLOT, f_bar);
                else tma2d(f_dst, (const CUtensorMap*)f_ptr, f_c0, f_c1, f_bar);
                if (i == 4) tma2d(f_dst + 8192, (const CUtensorMap*)f_ptr, f_c0, 256, f_bar);
            }
        }
        return;
    }

    if (warp == 9) {
        const uint32_t cnt0 = ld_rlx(scr->cnt + hkv * 32);
        const uint4 pz = make_uint4(POISON, POISON, POISON, POISON);
        st_rlx4(scr->q + (lane >> 2) * 2048 + cta * 16 + (lane & 3) * 4, pz);
        if (lane < 16 && cta < 112) st_rlx4(scr->h + cta * 64 + lane * 4, pz);
        if (lane < 2) st_rlx4(scr->st + cta * 8 + lane * 4, pz);
        st_rlx4(scr->o + cta * 256 + lane * 4, pz);
        st_rlx4(scr->o + cta * 256 + 128 + lane * 4, pz);
        if (lane < 16) st_rlx4(reinterpret_cast<uint32_t*>(scr->acc) + cta * 64 + lane * 4, make_uint4(0u, 0u, 0u, 0u));
        __syncwarp();
        bar_arrive288(3);
        const uint32_t target = (cnt0 & ~15u) + 16u;
        if (lane == 0) {
            asm volatile("fence.acq_rel.gpu;" ::: "memory");
            asm volatile("red.relaxed.gpu.global.add.u32 [%0], 1;" :: "l"(scr->cnt + hkv * 32) : "memory");
            #pragma unroll 1
            for (uint32_t n = 0; (int32_t)(ld_acq(scr->cnt + hkv * 32) - target) < 0; n++) if (n > SPIN_LIMIT) __trap();
        }
        __syncwarp();
        bar_sync288(5);
        mbar_wait0(bar_emptyA);
        __nanosleep(300);
        {
            const uint32_t* pq = scr->q + bb * 2048 + hkv * 256 + lane * 4;
            uint4 v0, v1;
            #pragma unroll 1
            for (uint32_t n = 0; ; n++) {
                v0 = ld_rlx4(pq); v1 = ld_rlx4(pq + 128);
                if (!__any_sync(0xffffffffu, has_poison(v0) || has_poison(v1))) break;
                if (n > SPIN_LIMIT) __trap();
            }
            const uint32_t a = sb + SM_Q + (lane >> 4) * 272 + (lane & 15) * 16;
            sts128(a, v0); sts128(a + 544, v1);
            __syncwarp();
            if (lane == 0) mbar_arrive(bar_q);
        }
        #pragma unroll 1
        for (uint32_t n = 0; __any_sync(0xffffffffu, (int32_t)(ld_acq(scr->cnt + (lane & 7) * 32) - target) < 0); n++)
            if (n > SPIN_LIMIT) __trap();
        mbar_wait0(bar_full + 12 * 8);
        {
            const uint32_t* p3 = lane < 16 ? scr->h + kg * 448 + 384 + lane * 4 : scr->st + (cta ^ 1) * 8 + (lane & 1) * 4;
            uint4 v[4];
            #pragma unroll 1
            for (uint32_t n = 0; ; n++) {
                #pragma unroll
                for (int i = 0; i < 3; i++) v[i] = ld_rlx4(scr->h + kg * 448 + i * 128 + lane * 4);
                v[3] = ld_rlx4(p3);
                if (!__any_sync(0xffffffffu, has_poison(v[0]) || has_poison(v[1]) || has_poison(v[2]) || has_poison(v[3]))) break;
                if (n > SPIN_LIMIT) __trap();
            }
            #pragma unroll
            for (int i = 0; i < 3; i++) sts128(sb + SM_H + i * 512 + lane * 16, v[i]);
            if (lane < 18) sts128(lane < 16 ? sb + SM_H + 1536 + lane * 16 : sb + SM_ST + (lane & 1) * 16, v[3]);
        }
        __syncwarp();
        if (lane == 0) mbar_arrive(bar_st);
        return;
    }

    const uint4 xa = *reinterpret_cast<const uint4*>(x + warp * 512 + lane * 8);
    const uint4 xb = *reinterpret_cast<const uint4*>(x + warp * 512 + 256 + lane * 8);
    if (lane == 0) {
        #pragma unroll 1
        for (int j = 5 + warp; j < NBAR; j += 8) mbar_init(bar_full + j * 8, j == NBAR - 1 ? 4 : 1);
        mbar_fence_init();
    }
    __syncwarp();
    bar_arrive288(4);
    bar_arrive288(5);
    {
        float xv[16];
        const uint32_t xw[8] = {xa.x, xa.y, xa.z, xa.w, xb.x, xb.y, xb.z, xb.w};
        #pragma unroll
        for (int i = 0; i < 8; i++) { xv[2 * i] = bf_lo(xw[i]); xv[2 * i + 1] = bf_hi(xw[i]); }
        float s = 0.f;
        #pragma unroll
        for (int i = 0; i < 16; i++) s += xv[i];
        #pragma unroll
        for (int o = 16; o; o >>= 1) s += __shfl_xor_sync(0xffffffffu, s, o);
        const float mean = s * (1.f / 512.f);
        float q = 0.f;
        #pragma unroll
        for (int i = 0; i < 16; i++) { const float d = xv[i] - mean; q += d * d; }
        #pragma unroll
        for (int o = 16; o; o >>= 1) q += __shfl_xor_sync(0xffffffffu, q, o);
        const float mb = bf16r(mean);
        const float den = bf16r(sqrt_approx(bf16r(bf16r(q * (1.f / 512.f)) + 1e-5f)));
        uint32_t o[8];
        #pragma unroll
        for (int i = 0; i < 8; i++)
            o[i] = pack_bf16(__fdividef(bf16r(xv[2 * i] - mb), den), __fdividef(bf16r(xv[2 * i + 1] - mb), den));
        sts128(sb + SM_XN + warp * 1040 + lane * 16, make_uint4(o[0], o[1], o[2], o[3]));
        sts128(sb + SM_XN + warp * 1040 + 512 + lane * 16, make_uint4(o[4], o[5], o[6], o[7]));
    }
    bar_sync288(2);
    bar_sync288(3);

    {
        uint32_t xf[4][2];
        #pragma unroll
        for (int s = 0; s < 4; s++) {
            const uint32_t a = sb + SM_XN + g * 1040 + (warp * 64 + s * 16 + 2 * t) * 2;
            xf[s][0] = lds32(a); xf[s][1] = lds32(a + 16);
        }
        float acc[3][4] = {};
        const int mi = lane >> 3, rr = lane & 7;
        const int krow = (warp & 3) * 64 + (mi >> 1) * 8 + rr;
        mbar_wait0(bar_full + (2 + (warp >> 2)) * 8);
        #pragma unroll
        for (int s = 0; s < 4; s++) {
            const int r = krow + s * 16;
            #pragma unroll
            for (int mt = 0; mt < 2; mt++) {
                uint32_t a[4];
                ldsm_x4_t(a, sb + (2 + (warp >> 2)) * SLOT + r * 64 + (((2 * mt + (mi & 1)) ^ ((r >> 1) & 3)) << 4));
                mma16816(acc[mt], a[0], a[1], a[2], a[3], xf[s][0], xf[s][1]);
            }
        }
        if (cta < 112) {
            mbar_wait0(bar_full + 4 * 8);
            #pragma unroll
            for (int s = 0; s < 4; s++) {
                const int r = (warp >> 2) * 256 + krow + s * 16;
                uint32_t a[4];
                ldsm_x4_t(a, sb + 4 * SLOT + r * 32 + (((mi & 1) ^ ((r >> 2) & 1)) << 4));
                mma16816(acc[2], a[0], a[1], a[2], a[3], xf[s][0], xf[s][1]);
            }
        }
        #pragma unroll
        for (int mt = 0; mt < 3; mt++)
            sts128(sb + SM_RED + (warp * 3 + mt) * 512 + lane * 16,
                   make_uint4(__float_as_uint(acc[mt][0]), __float_as_uint(acc[mt][1]), __float_as_uint(acc[mt][2]), __float_as_uint(acc[mt][3])));
    }
    bar_consumers();
    if (tid == 0) mbar_arrive(bar_emptyA);
    if (tid < 192) {
        const int tile = tid < 128 ? ((tid >> 3) & 1) : 2;
        const int b = tid < 128 ? (tid >> 4) : ((tid - 128) >> 3);
        const int j = tid & 7;
        const uint32_t a = sb + SM_RED + tile * 512 + (4 * ((2 * j) & 7) + (b >> 1)) * 16 + (2 * (j >> 2) + (b & 1)) * 4;
        float v0 = 0.f, v1 = 0.f;
        #pragma unroll
        for (int w = 0; w < 8; w++) { v0 += lds32f(a + w * 1536); v1 += lds32f(a + w * 1536 + 64); }
        if (tid < 128) {
            st_rlx(scr->q + b * 2048 + cta * 16 + (tid & 15), unpoison(pack_bf16(v0, v1)));
        } else if (cta < 112) {
            v0 = bf16r(v0); v1 = bf16r(v1);
            v0 = __fdividef(v0, 1.f + __expf(-v0));
            v1 = __fdividef(v1, 1.f + __expf(-v1));
            st_rlx(scr->h + cta * 64 + b * 8 + 2 * (j & 3) + (j >> 2), unpoison(pack_bf16(v0, v1)));
        }
    }

    float sc[4][4] = {};
    {
        uint4 qf[4];
        mbar_wait0(bar_q);
        #pragma unroll
        for (int j = 0; j < 4; j++) qf[j] = lds128(sb + SM_Q + (g & 3) * 272 + (4 * (j ^ (g >> 2)) + t) * 16);
        const int fill = warp < 2 ? warp : warp + 3;
        mbar_wait0(bar_full + fill * 8);
        const uint32_t kb = sb + fill * SLOT + g * 256 + t * 16;
        #pragma unroll
        for (int j = 0; j < 4; j++) {
            #pragma unroll
            for (int mt = 0; mt < 4; mt++) {
                const uint32_t a = kb + mt * 4096 + ((j ^ (g & 1)) << 6);
                const uint4 lo = lds128(a), hi = lds128(a + 2048);
                mma16816(sc[mt], lo.x, hi.x, lo.y, hi.y, qf[j].x, qf[j].y);
                mma16816(sc[mt], lo.z, hi.z, lo.w, hi.w, qf[j].z, qf[j].w);
            }
        }
        __syncwarp();
        if (lane == 0 && warp < 7) mbar_arrive(bar_emptyK + warp * 8);
    }
    const bool valid = (t >> 1) == (g & 1);
    const int h0 = 2 * (t & 1);
    {
        float m0 = -INFINITY, m1 = -INFINITY;
        #pragma unroll
        for (int mt = 0; mt < 4; mt++) {
            #pragma unroll
            for (int i = 0; i < 4; i++) sc[mt][i] = bf16r(bf16r(sc[mt][i]) * 0.08838834764831845f);
            m0 = fmaxf(m0, fmaxf(sc[mt][0], sc[mt][2]));
            m1 = fmaxf(m1, fmaxf(sc[mt][1], sc[mt][3]));
        }
        if (!valid) { m0 = -INFINITY; m1 = -INFINITY; }
        #pragma unroll
        for (int o = 2; o <= 16; o <<= 1) {
            m0 = fmaxf(m0, __shfl_xor_sync(0xffffffffu, m0, o));
            m1 = fmaxf(m1, __shfl_xor_sync(0xffffffffu, m1, o));
        }
        if (lane < 2) { sts32f(sb + SM_WMAX + warp * 16 + h0 * 4, m0); sts32f(sb + SM_WMAX + warp * 16 + h0 * 4 + 4, m1); }
    }
    bar_consumers();
    float mloc0 = -INFINITY, mloc1 = -INFINITY;
    {
        #pragma unroll
        for (int w = 0; w < 8; w++) {
            mloc0 = fmaxf(mloc0, lds32f(sb + SM_WMAX + w * 16 + h0 * 4));
            mloc1 = fmaxf(mloc1, lds32f(sb + SM_WMAX + w * 16 + h0 * 4 + 4));
        }
        const float L2E = 1.4426950408889634f;
        float l0 = 0.f, l1 = 0.f;
        const uint32_t pa = sb + SM_P + (h0 * 260 + warp * 32 + (g & 3) * 8 + (g >> 2)) * 4;
        #pragma unroll
        for (int mt = 0; mt < 4; mt++) {
            const float p0 = ex2((sc[mt][0] - mloc0) * L2E), p2 = ex2((sc[mt][2] - mloc0) * L2E);
            const float p1 = ex2((sc[mt][1] - mloc1) * L2E), p3 = ex2((sc[mt][3] - mloc1) * L2E);
            l0 += p0 + p2; l1 += p1 + p3;
            if (valid) { sts32(pa + mt * 8, pack_bf16(p0, p2)); sts32(pa + 1040 + mt * 8, pack_bf16(p1, p3)); }
        }
        if (!valid) { l0 = 0.f; l1 = 0.f; }
        #pragma unroll
        for (int o = 2; o <= 16; o <<= 1) {
            l0 += __shfl_xor_sync(0xffffffffu, l0, o);
            l1 += __shfl_xor_sync(0xffffffffu, l1, o);
        }
        if (lane < 2) { sts32f(sb + SM_WSUM + warp * 16 + h0 * 4, l0); sts32f(sb + SM_WSUM + warp * 16 + h0 * 4 + 4, l1); }
    }
    bar_consumers();
    float lloc0 = 0.f, lloc1 = 0.f;
    #pragma unroll
    for (int w = 0; w < 8; w++) {
        lloc0 += lds32f(sb + SM_WSUM + w * 16 + h0 * 4);
        lloc1 += lds32f(sb + SM_WSUM + w * 16 + h0 * 4 + 4);
    }
    if (tid < 2) {
        st_rlx(scr->st + cta * 8 + h0, unpoison(__float_as_uint(mloc0)));
        st_rlx(scr->st + cta * 8 + h0 + 1, unpoison(__float_as_uint(mloc1)));
        st_rlx(scr->st + cta * 8 + 4 + h0, unpoison(__float_as_uint(lloc0)));
        st_rlx(scr->st + cta * 8 + 4 + h0 + 1, unpoison(__float_as_uint(lloc1)));
    }

    float oa[4][4] = {};
    uint32_t* pub = scr->o + cta * 256 + h0 * 64 + warp * 8 + g;
    keep64(pub);
    float scale0 = 0.f, scale1 = 0.f;
    {
        const int mi = lane >> 3, rr = lane & 7;
        const int key = (rr >> 1) + 4 * (mi >> 1) + 8 * (rr & 1);
        const int rowp = 2 * key + (warp >> 2);
        const uint32_t voff = rowp * 128 + (((2 * (warp & 3) + (mi & 1)) ^ (rowp & 7)) << 4);
        #pragma unroll 1
        for (int vc = 0; vc < 8; vc++) {
            uint4 p0 = make_uint4(0u, 0u, 0u, 0u), p1 = p0;
            if (g < 4) {
                const uint32_t a = sb + SM_P + (g * 260 + vc * 32 + t * 8) * 4;
                p0 = lds128(a); p1 = lds128(a + 16);
            }
            if (vc == 7) {
                mbar_wait0(bar_st);
                const float L2E = 1.4426950408889634f;
                const float mo0 = lds32f(sb + SM_ST + h0 * 4), mo1 = lds32f(sb + SM_ST + h0 * 4 + 4);
                const float mg0 = fmaxf(mloc0, mo0), mg1 = fmaxf(mloc1, mo1);
                const float e0 = ex2((mloc0 - mg0) * L2E), e1 = ex2((mloc1 - mg1) * L2E);
                scale0 = __fdividef(e0, lloc0 * e0 + lds32f(sb + SM_ST + 16 + h0 * 4) * ex2((mo0 - mg0) * L2E));
                scale1 = __fdividef(e1, lloc1 * e1 + lds32f(sb + SM_ST + 20 + h0 * 4) * ex2((mo1 - mg1) * L2E));
            }
            const int fill = 11 + vc, slot = vc == 0 ? 11 : (vc < 4 ? vc + 1 : (vc < 6 ? vc - 4 : vc - 1));
            mbar_wait0(bar_full + fill * 8);
            const uint32_t vb = sb + slot * SLOT + voff;
            uint32_t a0[4], a1[4], a2[4], a3[4];
            ldsm_x4_t(a0, vb); ldsm_x4_t(a1, vb + 4096); ldsm_x4_t(a2, vb + 8192); ldsm_x4_t(a3, vb + 12288);
            mma16816(oa[0], a0[0], a0[1], a0[2], a0[3], p0.x, p0.y);
            mma16816(oa[1], a1[0], a1[1], a1[2], a1[3], p0.z, p0.w);
            mma16816(oa[2], a2[0], a2[1], a2[2], a2[3], p1.x, p1.y);
            mma16816(oa[3], a3[0], a3[1], a3[2], a3[3], p1.z, p1.w);
        }
        float os[4];
        #pragma unroll
        for (int i = 0; i < 4; i++) os[i] = (oa[0][i] + oa[1][i]) + (oa[2][i] + oa[3][i]);
        const uint32_t lo = pack_bf16(os[0] * scale0, os[1] * scale1);
        const uint32_t hi = pack_bf16(os[2] * scale0, os[3] * scale1);
        const bool odd = g & 1;
        const uint32_t y = __shfl_xor_sync(0xffffffffu, odd ? lo : hi, 4);
        const uint32_t first = odd ? y : lo, second = odd ? hi : y;
        if (t < 2) {
            st_rlx(pub, unpoison(__byte_perm(first, second, 0x5410)));
            st_rlx(pub + 64, unpoison(__byte_perm(first, second, 0x7632)));
        }
    }

    if (warp >= 4) {
        const uint32_t* po = scr->o + (hkv * 16 + (warp - 4) * 4) * 256 + (kg & 1) * 128 + lane * 4;
        uint32_t so = sb + SM_O + (warp - 4) * 1152 + (lane >> 2) * 64 + (lane & 1) * 32 + (lane & 2) * 4;
        keep64(po); keep32(so);
        mbar_wait0(bar_full + 20 * 8);
        for (const uint32_t c0 = clk32(); clk32() - c0 < 200u;) {}
        uint4 v[4];
        #pragma unroll
        for (int i = 0; i < 4; i++) v[i] = ld_rlx4(po + i * 256);
        #pragma unroll 1
        for (uint32_t n = 0; ; n++) {
            bool bad[4];
            #pragma unroll
            for (int i = 0; i < 4; i++) bad[i] = __any_sync(0xffffffffu, has_poison(v[i]));
            if (!(bad[0] || bad[1] || bad[2] || bad[3])) break;
            #pragma unroll
            for (int i = 0; i < 4; i++) if (bad[i]) v[i] = ld_rlx4(po + i * 256);
            if (n > SPIN_LIMIT) __trap();
        }
        #pragma unroll
        for (int i = 0; i < 2; i++) {
            sts64(so + i * 576, hadd2_bf16(v[2 * i].x, v[2 * i + 1].x), hadd2_bf16(v[2 * i].y, v[2 * i + 1].y));
            sts64(so + i * 576 + 16, hadd2_bf16(v[2 * i].z, v[2 * i + 1].z), hadd2_bf16(v[2 * i].w, v[2 * i + 1].w));
        }
        __syncwarp();
        if (lane == 0) mbar_arrive(bar_o);
        return;
    }
    {
        float acc[8][4] = {};
        uint32_t wa[4][4][4];
        const int mi = lane >> 3, rr = lane & 7;
        uint32_t wb = sb + 8 * SLOT + ((mi >> 1) * 8 + rr) * 128 + (((2 * warp + (mi & 1)) ^ rr) << 4);
        uint32_t so = sb + SM_O + g * 576 + t * 16;
        const int ocol = 64 * cg + 16 * warp + g;
        float* pacc = scr->acc + (cg * 4 + warp) * 256 + lane * 4;
        __nv_bfloat16* pout = out + 2 * t * 512 + ocol;
        keep32(wb); keep32(so); keep64(pacc); keep64(pout);
        const __nv_bfloat16* px = x + 2 * t * 512 + ocol;
        const __nv_bfloat16 b0 = px[0], b1 = px[512], b2 = px[8], b3 = px[520];
        mbar_wait0(bar_full + 19 * 8);
        #pragma unroll
        for (int i = 0; i < 7; i++) {
            uint32_t a[4];
            ldsm_x4_t(a, wb - SLOT + i * 2048);
            const uint32_t ha = sb + SM_H + i * 256 + lane * 8;
            mma16816(acc[i], a[0], a[1], a[2], a[3], lds32(ha), lds32(ha + 4));
        }
        float x0 = __bfloat162float(b0), x1 = __bfloat162float(b1), x2 = __bfloat162float(b2), x3 = __bfloat162float(b3);
        keepf(x0); keepf(x1); keepf(x2); keepf(x3);
        #pragma unroll
        for (int pc = 0; pc < 3; pc++) {
            mbar_wait0(bar_full + (20 + pc) * 8);
            #pragma unroll
            for (int k = 0; k < 4; k++) ldsm_x4_t(wa[pc][k], wb + pc * 8192 + k * 2048);
        }
        bool o_first;
        #pragma unroll 1
        for (uint32_t n = 0; ; n++) {
            o_first = mbar_test0(bar_o);
            if (o_first || mbar_test0(bar_full + 23 * 8)) break;
            if (n > SPIN_LIMIT * 16) __trap();
        }
        uint4 of[8];
        if (!o_first) {
            #pragma unroll
            for (int k = 0; k < 4; k++) ldsm_x4_t(wa[3][k], wb + 24576 + k * 2048);
            mbar_wait0(bar_o);
        }
        #pragma unroll
        for (int i = 0; i < 8; i++) of[i] = lds128(so + i * 64);
        #pragma unroll
        for (int pc = 0; pc < 3; pc++) {
            #pragma unroll
            for (int k = 0; k < 4; k++) {
                const uint4& u = of[2 * pc + (k >> 1)];
                mma16816(acc[(pc & 1) * 4 + k], wa[pc][k][0], wa[pc][k][1], wa[pc][k][2], wa[pc][k][3], k & 1 ? u.z : u.x, k & 1 ? u.w : u.y);
            }
        }
        if (o_first) {
            #pragma unroll
            for (int i = 0; i < 4; i++) acc[0][i] = (acc[0][i] + acc[1][i]) + (acc[2][i] + acc[3][i]);
            mbar_wait0(bar_full + 23 * 8);
            #pragma unroll
            for (int k = 0; k < 4; k++) ldsm_x4_t(wa[3][k], wb + 24576 + k * 2048);
        }
        #pragma unroll
        for (int k = 0; k < 4; k++) {
            const uint4& u = of[6 + (k >> 1)];
            mma16816(acc[4 + k], wa[3][k][0], wa[3][k][1], wa[3][k][2], wa[3][k][3], k & 1 ? u.z : u.x, k & 1 ? u.w : u.y);
        }
        if (!o_first) {
            #pragma unroll
            for (int i = 0; i < 4; i++) acc[0][i] = (acc[0][i] + acc[1][i]) + (acc[2][i] + acc[3][i]);
        }
        float r[4];
        #pragma unroll
        for (int i = 0; i < 4; i++) r[i] = (acc[4][i] + acc[5][i]) + (acc[6][i] + acc[7][i]) + acc[0][i];
        float4 o0, o1;
        asm volatile("atom.relaxed.gpu.global.add.v4.f32 {%0,%1,%2,%3}, [%4], {%5,%6,%7,%8};"
                     : "=f"(o0.x), "=f"(o0.y), "=f"(o0.z), "=f"(o0.w) : "l"(pacc), "f"(r[0]), "f"(r[1]), "f"(1.f), "f"(0.f) : "memory");
        asm volatile("atom.relaxed.gpu.global.add.v4.f32 {%0,%1,%2,%3}, [%4], {%5,%6,%7,%8};"
                     : "=f"(o1.x), "=f"(o1.y), "=f"(o1.z), "=f"(o1.w) : "l"(pacc + 128), "f"(r[2]), "f"(r[3]), "f"(1.f), "f"(0.f) : "memory");
        r[0] += x0; r[1] += x1; r[2] += x2; r[3] += x3;
        if (o0.z == 15.f) {
            pout[0] = __float2bfloat16_rn(o0.x + r[0]);
            pout[512] = __float2bfloat16_rn(o0.y + r[1]);
        }
        if (o1.z == 15.f) {
            pout[8] = __float2bfloat16_rn(o1.x + r[2]);
            pout[520] = __float2bfloat16_rn(o1.y + r[3]);
        }
    }
}

typedef CUresult (*EncodeTiledFn)(CUtensorMap*, CUtensorMapDataType, cuuint32_t, void*, const cuuint64_t*, const cuuint64_t*,
                                  const cuuint32_t*, const cuuint32_t*, CUtensorMapInterleave, CUtensorMapSwizzle,
                                  CUtensorMapL2promotion, CUtensorMapFloatOOBfill);

void make_map(EncodeTiledFn enc, CUtensorMap* m, const void* base, uint64_t cols, uint64_t rows, uint32_t box_cols,
              uint32_t box_rows, CUtensorMapSwizzle sw) {
    cuuint64_t gd[2] = {cols, rows};
    cuuint64_t gs[1] = {cols * 2};
    cuuint32_t bd[2] = {box_cols, box_rows};
    cuuint32_t es[2] = {1, 1};
    enc(m, CU_TENSOR_MAP_DATA_TYPE_BFLOAT16, 2, const_cast<void*>(base), gd, gs, bd, es, CU_TENSOR_MAP_INTERLEAVE_NONE, sw,
        CU_TENSOR_MAP_L2_PROMOTION_L2_256B, CU_TENSOR_MAP_FLOAT_OOB_FILL_NONE);
}

}

extern "C" void kernel_launch(void* const* d_in, const int* in_sizes, int n_in, void* d_out, int out_size) {
    (void)in_sizes; (void)n_in; (void)out_size;
    static EncodeTiledFn enc = nullptr;
    static Scratch* scr = nullptr;
    if (!enc) {
        cudaGetSymbolAddress((void**)&scr, g_scratch);
        void* fn = nullptr;
        cudaDriverEntryPointQueryResult qr;
        cudaGetDriverEntryPoint("cuTensorMapEncodeTiled", &fn, cudaEnableDefault, &qr);
        enc = (EncodeTiledFn)fn;
        cudaFuncSetAttribute(fused_decode_kernel, cudaFuncAttributeMaxDynamicSharedMemorySize, SMEM_BYTES);
    }
    TMaps tm;
    make_map(enc, &tm.wq, d_in[3], 4096, 512, 32, 256, CU_TENSOR_MAP_SWIZZLE_64B);
    make_map(enc, &tm.w1, d_in[6], 1792, 512, 16, 256, CU_TENSOR_MAP_SWIZZLE_32B);
    make_map(enc, &tm.v, d_in[2], 64, 8ull * 8 * 4096 * 2, 64, 128, CU_TENSOR_MAP_SWIZZLE_128B);
    make_map(enc, &tm.wo, d_in[4], 512, 4096, 64, 64, CU_TENSOR_MAP_SWIZZLE_128B);
    make_map(enc, &tm.w2, d_in[7], 512, 1792, 64, 112, CU_TENSOR_MAP_SWIZZLE_128B);
    fused_decode_kernel<<<NCTA, NTHREADS, SMEM_BYTES, cudaStreamPerThread>>>(
        (const __nv_bfloat16*)d_in[1], (const __nv_bfloat16*)d_in[0], (__nv_bfloat16*)d_out, scr,
        tm);
}
```

```cpp
#include <cuda_runtime.h>
#include <cuda_bf16.h>
#include <cuda.h>
#include <stdint.h>

namespace {

constexpr int NCTA = 128;
constexpr int NTHREADS = 320;
constexpr int SLOT = 16384;
constexpr int NSLOT = 12;
constexpr int NFILL = 24;
constexpr uint32_t POISON = 0xFFFFFFFFu;
constexpr uint32_t SPIN_LIMIT = 1u << 21;

constexpr int PACE_T0 = 500, PACE_TAU = 653, PACE_TAIL_FROM = 16, PACE_TAIL_EXTRA = 70;

constexpr int SM_XN = NSLOT * SLOT;
constexpr int SM_RED = SM_XN + 8 * 1040;
constexpr int SM_P = SM_RED + 8 * 3 * 512;
constexpr int SM_WMAX = SM_P + 4 * 260 * 4;
constexpr int SM_WSUM = SM_WMAX + 128;
constexpr int SM_ST = SM_WSUM + 128;
constexpr int SM_Q = SM_ST + 32;
constexpr int SM_H = SM_Q + 4 * 272;
constexpr int SM_O = SM_RED;
constexpr int SM_BAR = SM_H + 7 * 256;
constexpr int NBAR = NFILL + 7 + 4;
constexpr int SM_TOTAL = SM_BAR + NBAR * 8;
constexpr int SMEM_BYTES = SM_TOTAL + 1024;

struct TMaps { CUtensorMap wq, w1, v, wo, w2; };

struct Scratch {
    float acc[8 * 4 * 2 * 128];
    uint32_t o[NCTA * 256];
    uint32_t q[8 * 2048];
    uint32_t h[112 * 64];
    uint32_t st[NCTA * 8];
    uint32_t cnt[8 * 32];
};
__device__ __align__(128) Scratch g_scratch;

__device__ __forceinline__ uint32_t gtime32() { uint32_t c; asm volatile("mov.u32 %0, %globaltimer_lo;" : "=r"(c)); return c; }
__device__ __forceinline__ uint32_t smem_u32(const void* p) { return (uint32_t)__cvta_generic_to_shared(p); }

__device__ __forceinline__ void mbar_init(uint32_t bar, uint32_t cnt) {
    asm volatile("mbarrier.init.shared::cta.b64 [%0], %1;" :: "r"(bar), "r"(cnt) : "memory");
}
__device__ __forceinline__ void mbar_fence_init() { asm volatile("fence.mbarrier_init.release.cluster;" ::: "memory"); }
__device__ __forceinline__ void mbar_expect_tx(uint32_t bar, uint32_t bytes) {
    asm volatile("mbarrier.arrive.expect_tx.shared::cta.b64 _, [%0], %1;" :: "r"(bar), "r"(bytes) : "memory");
}
__device__ __forceinline__ void mbar_arrive(uint32_t bar) {
    asm volatile("mbarrier.arrive.shared::cta.b64 _, [%0];" :: "r"(bar) : "memory");
}
__device__ __forceinline__ void mbar_wait0(uint32_t bar) {
    #pragma unroll 1
    for (uint32_t i = 0; i < SPIN_LIMIT; i++) {
        uint32_t ok;
        asm volatile("{\n.reg .pred p;\nmbarrier.try_wait.parity.shared::cta.b64 p, [%1], 0;\nselp.u32 %0, 1, 0, p;\n}"
                     : "=r"(ok) : "r"(bar) : "memory");
        if (ok) return;
    }
    __trap();
}
constexpr uint64_t EVICT_FIRST = 0x12F0000000000000ull;
__device__ __forceinline__ void bulk_g2s(uint32_t dst, const void* src, uint32_t bytes, uint32_t bar) {
    asm volatile("cp.async.bulk.shared::cluster.global.mbarrier::complete_tx::bytes.L2::cache_hint [%0], [%1], %2, [%3], %4;"
                 :: "r"(dst), "l"(src), "r"(bytes), "r"(bar), "l"(EVICT_FIRST) : "memory");
}
__device__ __forceinline__ void tma2d(uint32_t dst, const CUtensorMap* tm, int c0, int c1, uint32_t bar) {
    asm volatile("cp.async.bulk.tensor.2d.shared::cluster.global.mbarrier::complete_tx::bytes.L2::cache_hint [%0], [%1, {%3, %4}], [%2], %5;"
                 :: "r"(dst), "l"(tm), "r"(bar), "r"(c0), "r"(c1), "l"(EVICT_FIRST) : "memory");
}
__device__ __forceinline__ void bar_consumers() { asm volatile("bar.sync 1, 256;" ::: "memory"); }
__device__ __forceinline__ void bar_sync288(int id) { asm volatile("bar.sync %0, 288;" :: "r"(id) : "memory"); }
__device__ __forceinline__ void bar_arrive288(int id) { asm volatile("bar.arrive %0, 288;" :: "r"(id) : "memory"); }
template <typename T> __device__ __forceinline__ void keep64(T*& p) { asm volatile("" : "+l"(p)); }
__device__ __forceinline__ void keep32(uint32_t& v) { asm volatile("" : "+r"(v)); }
__device__ __forceinline__ void keepf(float& v) { asm volatile("" : "+f"(v)); }
__device__ __forceinline__ uint32_t hadd2_bf16(uint32_t a, uint32_t b) {
    uint32_t r; asm("add.rn.bf16x2 %0, %1, %2;" : "=r"(r) : "r"(a), "r"(b)); return r;
}

__device__ __forceinline__ uint4 lds128(uint32_t a) {
    uint4 v; asm volatile("ld.shared.v4.u32 {%0,%1,%2,%3}, [%4];" : "=r"(v.x), "=r"(v.y), "=r"(v.z), "=r"(v.w) : "r"(a)); return v;
}
__device__ __forceinline__ uint32_t lds32(uint32_t a) { uint32_t v; asm volatile("ld.shared.u32 %0, [%1];" : "=r"(v) : "r"(a)); return v; }
__device__ __forceinline__ float lds32f(uint32_t a) { float v; asm volatile("ld.shared.f32 %0, [%1];" : "=f"(v) : "r"(a)); return v; }
__device__ __forceinline__ void sts32(uint32_t a, uint32_t v) { asm volatile("st.shared.u32 [%0], %1;" :: "r"(a), "r"(v) : "memory"); }
__device__ __forceinline__ void sts32f(uint32_t a, float v) { asm volatile("st.shared.f32 [%0], %1;" :: "r"(a), "f"(v) : "memory"); }
__device__ __forceinline__ void sts64(uint32_t a, uint32_t x, uint32_t y) {
    asm volatile("st.shared.v2.u32 [%0], {%1,%2};" :: "r"(a), "r"(x), "r"(y) : "memory");
}
__device__ __forceinline__ void sts128(uint32_t a, uint4 v) {
    asm volatile("st.shared.v4.u32 [%0], {%1,%2,%3,%4};" :: "r"(a), "r"(v.x), "r"(v.y), "r"(v.z), "r"(v.w) : "memory");
}
__device__ __forceinline__ void ldsm_x4_t(uint32_t (&r)[4], uint32_t a) {
    asm volatile("ldmatrix.sync.aligned.m8n8.x4.trans.shared.b16 {%0,%1,%2,%3}, [%4];"
                 : "=r"(r[0]), "=r"(r[1]), "=r"(r[2]), "=r"(r[3]) : "r"(a));
}
__device__ __forceinline__ void mma16816(float (&c)[4], uint32_t a0, uint32_t a1, uint32_t a2, uint32_t a3, uint32_t b0, uint32_t b1) {
    asm volatile("mma.sync.aligned.m16n8k16.row.col.f32.bf16.bf16.f32 {%0,%1,%2,%3}, {%4,%5,%6,%7}, {%8,%9}, {%0,%1,%2,%3};"
                 : "+f"(c[0]), "+f"(c[1]), "+f"(c[2]), "+f"(c[3]) : "r"(a0), "r"(a1), "r"(a2), "r"(a3), "r"(b0), "r"(b1));
}

__device__ __forceinline__ uint32_t ld_rlx(const uint32_t* p) {
    uint32_t v; asm volatile("ld.relaxed.gpu.global.u32 %0, [%1];" : "=r"(v) : "l"(p) : "memory"); return v;
}
__device__ __forceinline__ uint32_t ld_acq(const uint32_t* p) {
    uint32_t v; asm volatile("ld.acquire.gpu.global.u32 %0, [%1];" : "=r"(v) : "l"(p) : "memory"); return v;
}
__device__ __forceinline__ uint4 ld_rlx4(const uint32_t* p) {
    uint4 v; asm volatile("ld.relaxed.gpu.global.v4.u32 {%0,%1,%2,%3}, [%4];" : "=r"(v.x), "=r"(v.y), "=r"(v.z), "=r"(v.w) : "l"(p) : "memory"); return v;
}
__device__ __forceinline__ void publish(uint32_t* p, uint32_t v) {
    asm volatile("red.relaxed.gpu.global.and.b32 [%0], %1;" :: "l"(p), "r"(v == POISON ? 0x7FFFFFFFu : v) : "memory");
}
__device__ __forceinline__ void st_rlx4(uint32_t* p, uint4 v) {
    asm volatile("st.relaxed.gpu.global.v4.u32 [%0], {%1,%2,%3,%4};" :: "l"(p), "r"(v.x), "r"(v.y), "r"(v.z), "r"(v.w) : "memory");
}
__device__ __forceinline__ bool has_poison(const uint4& v) {
    return v.x == POISON || v.y == POISON || v.z == POISON || v.w == POISON;
}

__device__ __forceinline__ float sqrt_approx(float x) { float r; asm("sqrt.approx.f32 %0, %1;" : "=f"(r) : "f"(x)); return r; }
__device__ __forceinline__ float ex2(float x) { float r; asm("ex2.approx.ftz.f32 %0, %1;" : "=f"(r) : "f"(x)); return r; }
__device__ __forceinline__ float bf16r(float x) { return __bfloat162float(__float2bfloat16_rn(x)); }
__device__ __forceinline__ uint32_t pack_bf16(float lo, float hi) {
    uint32_t r; asm("cvt.rn.bf16x2.f32 %0, %1, %2;" : "=r"(r) : "f"(hi), "f"(lo)); return r;
}
__device__ __forceinline__ float bf_lo(uint32_t w) { return __uint_as_float(w << 16); }
__device__ __forceinline__ float bf_hi(uint32_t w) { return __uint_as_float(w & 0xFFFF0000u); }

__device__ __forceinline__ void tail_stage(const uint32_t sb, const int kg, const int cg, Scratch* __restrict__ scr,
                                        const __nv_bfloat16* __restrict__ x, __nv_bfloat16* __restrict__ out)
{
    const int tid = threadIdx.x, warp = tid >> 5, lane = tid & 31, g = lane >> 2, t = lane & 3;
    const uint32_t bar_full = sb + SM_BAR, bar_o = bar_full + (NBAR - 1) * 8;
    if (warp >= 4) {
        const uint32_t* po = scr->o + ((kg >> 1) * 16 + (warp - 4) * 4) * 256 + (kg & 1) * 128 + lane * 4;
        uint32_t so = sb + SM_O + (warp - 4) * 1152 + (lane >> 2) * 64 + (lane & 1) * 32 + (lane & 2) * 4;
        keep64(po); keep32(so);
        mbar_wait0(bar_full + 19 * 8);
        uint4 v[4];
        #pragma unroll
        for (int i = 0; i < 4; i++) v[i] = ld_rlx4(po + i * 256);
        #pragma unroll 1
        for (uint32_t n = 0; ; n++) {
            bool bad[4];
            #pragma unroll
            for (int i = 0; i < 4; i++) bad[i] = __any_sync(0xffffffffu, has_poison(v[i]));
            if (!(bad[0] || bad[1] || bad[2] || bad[3])) break;
            #pragma unroll
            for (int i = 0; i < 4; i++) if (bad[i]) v[i] = ld_rlx4(po + i * 256);
            if (n > SPIN_LIMIT) __trap();
        }
        #pragma unroll
        for (int i = 0; i < 2; i++) {
            sts64(so + i * 576, hadd2_bf16(v[2 * i].x, v[2 * i + 1].x), hadd2_bf16(v[2 * i].y, v[2 * i + 1].y));
            sts64(so + i * 576 + 16, hadd2_bf16(v[2 * i].z, v[2 * i + 1].z), hadd2_bf16(v[2 * i].w, v[2 * i + 1].w));
        }
        __syncwarp();
        if (lane == 0) mbar_arrive(bar_o);
        return;
    }
    float acc[8][4] = {};
    uint32_t wa[4][4][4];
    const int mi = lane >> 3, rr = lane & 7;
    uint32_t wb = sb + 8 * SLOT + ((mi >> 1) * 8 + rr) * 128 + (((2 * warp + (mi & 1)) ^ rr) << 4);
    uint32_t so = sb + SM_O + g * 576 + t * 16;
    const int ocol = 64 * cg + 16 * warp + g;
    float* pacc = scr->acc + (cg * 4 + warp) * 256 + lane * 4;
    __nv_bfloat16* pout = out + 2 * t * 512 + ocol;
    keep32(wb); keep32(so); keep64(pacc); keep64(pout);
    const __nv_bfloat16* px = x + 2 * t * 512 + ocol;
    const __nv_bfloat16 b0 = px[0], b1 = px[512], b2 = px[8], b3 = px[520];
    mbar_wait0(bar_full + 19 * 8);
    #pragma unroll
    for (int i = 0; i < 7; i++) {
        uint32_t a[4];
        ldsm_x4_t(a, wb - SLOT + i * 2048);
        const uint32_t ha = sb + SM_H + i * 256 + lane * 8;
        mma16816(acc[i], a[0], a[1], a[2], a[3], lds32(ha), lds32(ha + 4));
    }
    float x0 = __bfloat162float(b0), x1 = __bfloat162float(b1), x2 = __bfloat162float(b2), x3 = __bfloat162float(b3);
    keepf(x0); keepf(x1); keepf(x2); keepf(x3);
    uint4 of[8];
    #pragma unroll
    for (int pc = 0; pc < 3; pc++) {
        mbar_wait0(bar_full + (20 + pc) * 8);
        #pragma unroll
        for (int k = 0; k < 4; k++) ldsm_x4_t(wa[pc][k], wb + pc * 8192 + k * 2048);
    }
    mbar_wait0(bar_o);
    #pragma unroll
    for (int i = 0; i < 8; i++) of[i] = lds128(so + i * 64);
    #pragma unroll
    for (int pc = 0; pc < 4; pc++) {
        if (pc == 3) {
            #pragma unroll
            for (int i = 0; i < 4; i++) acc[0][i] = (acc[0][i] + acc[1][i]) + (acc[2][i] + acc[3][i]);
            mbar_wait0(bar_full + (20 + pc) * 8);
            #pragma unroll
            for (int k = 0; k < 4; k++) ldsm_x4_t(wa[pc][k], wb + pc * 8192 + k * 2048);
        }
        #pragma unroll
        for (int k = 0; k < 4; k++) {
            const uint4& u = of[2 * pc + (k >> 1)];
            mma16816(acc[(pc & 1) * 4 + k], wa[pc][k][0], wa[pc][k][1], wa[pc][k][2], wa[pc][k][3], k & 1 ? u.z : u.x, k & 1 ? u.w : u.y);
        }
    }
    float r[4];
    #pragma unroll
    for (int i = 0; i < 4; i++) r[i] = (acc[4][i] + acc[5][i]) + (acc[6][i] + acc[7][i]) + acc[0][i];
    float4 o0, o1;
    asm volatile("atom.relaxed.gpu.global.add.v4.f32 {%0,%1,%2,%3}, [%4], {%5,%6,%7,%8};"
                 : "=f"(o0.x), "=f"(o0.y), "=f"(o0.z), "=f"(o0.w) : "l"(pacc), "f"(r[0]), "f"(r[1]), "f"(1.f), "f"(0.f) : "memory");
    asm volatile("atom.relaxed.gpu.global.add.v4.f32 {%0,%1,%2,%3}, [%4], {%5,%6,%7,%8};"
                 : "=f"(o1.x), "=f"(o1.y), "=f"(o1.z), "=f"(o1.w) : "l"(pacc + 128), "f"(r[2]), "f"(r[3]), "f"(1.f), "f"(0.f) : "memory");
    r[0] += x0; r[1] += x1; r[2] += x2; r[3] += x3;
    if (o0.z == 15.f) {
        pout[0] = __float2bfloat16_rn(o0.x + r[0]);
        pout[512] = __float2bfloat16_rn(o0.y + r[1]);
    }
    if (o1.z == 15.f) {
        pout[8] = __float2bfloat16_rn(o1.x + r[2]);
        pout[520] = __float2bfloat16_rn(o1.y + r[3]);
    }
}

__global__ void __launch_bounds__(NTHREADS, 1)
fused_decode_kernel(const __nv_bfloat16* __restrict__ kcache, const __nv_bfloat16* __restrict__ x,
                    __nv_bfloat16* __restrict__ out, Scratch* __restrict__ scr,
                    const __grid_constant__ TMaps tm)
{
    extern __shared__ uint8_t smem_raw[];
    const uint32_t sb = (smem_u32(smem_raw) + 1023u) & ~1023u;
    const int tid = threadIdx.x, warp = tid >> 5, lane = tid & 31;
    const int cta = blockIdx.x;
    const int hkv = cta >> 4, bb = (cta >> 1) & 7, half = cta & 1;
    const int kg = cta >> 3, cg = cta & 7;
    const int g = lane >> 2, t = lane & 3;
    const uint32_t bar_full = sb + SM_BAR, bar_emptyK = bar_full + NFILL * 8, bar_emptyA = bar_emptyK + 7 * 8;
    const uint32_t bar_q = bar_emptyA + 8, bar_st = bar_q + 8;

    const int kvrow0 = (bb * 8 + hkv) * 4096 + 3072 + half * 512;
    uint32_t t_start = 0;
    if (tid == 0)
        asm volatile("cp.async.bulk.prefetch.L2.global.L2::cache_hint [%0], %1, %2;"
                     :: "l"(kcache + (size_t)kvrow0 * 128), "r"(2 * SLOT), "l"(EVICT_FIRST) : "memory");
    if (tid == 256) {
        mbar_init(bar_full, 1);
        mbar_init(bar_full + 8, 1);
        mbar_fence_init();
        mbar_expect_tx(bar_full, SLOT);
        bulk_g2s(sb, kcache + (size_t)kvrow0 * 128, SLOT, bar_full);
        mbar_expect_tx(bar_full + 8, SLOT);
        bulk_g2s(sb + SLOT, kcache + (size_t)(kvrow0 + 64) * 128, SLOT, bar_full + 8);
        t_start = gtime32();
    }

    if (warp == 8) {
        if (lane == 0) {
            asm volatile("prefetch.tensormap [%0];" :: "l"(&tm.wq));
            asm volatile("prefetch.tensormap [%0];" :: "l"(&tm.w1));
            asm volatile("prefetch.tensormap [%0];" :: "l"(&tm.v));
            asm volatile("prefetch.tensormap [%0];" :: "l"(&tm.wo));
            asm volatile("prefetch.tensormap [%0];" :: "l"(&tm.w2));
            mbar_init(bar_full + 16, 1); mbar_init(bar_full + 24, 1); mbar_init(bar_full + 32, 1);
            mbar_fence_init();
        }
        __syncwarp();
        bar_arrive288(2);
        const int i = lane;
        const int slot = i < NSLOT ? i : (i < 15 ? i - 10 : (i < 17 ? i - 15 : (i < 20 ? i - NSLOT : 8 + ((i - 20) >> 1))));
        const uint32_t f_empty = i < NSLOT ? 0u : (i < 15 ? bar_emptyA : bar_emptyK + (slot < 2 ? slot : slot - 3) * 8);
        const uint32_t f_bar = bar_full + i * 8;
        const uint32_t f_dst = sb + slot * SLOT + (i >= 20 ? (i & 1) * 8192 : 0);
        const uint32_t f_bytes = i >= 20 ? SLOT / 2 : (i == 19 ? 112 * 128 : SLOT);
        const bool f_bulk = i >= 5 && i <= 10;
        const void* f_ptr = i <= 3 ? (const void*)&tm.wq : i == 4 ? (const void*)&tm.w1
                          : f_bulk ? (const void*)(kcache + (size_t)(kvrow0 + ((i - 3) & 7) * 64) * 128)
                          : i <= 18 ? (const void*)&tm.v : i == 19 ? (const void*)&tm.w2 : (const void*)&tm.wo;
        const int f_c0 = i <= 3 ? cta * 32 : i == 4 ? cta * 16 : i <= 18 ? 0 : cg * 64;
        const int f_c1 = i <= 3 ? (i - 2) * 256 : i == 4 ? 0 : i <= 18 ? (kvrow0 + ((i - 11) & 7) * 64) * 2
                       : i == 19 ? kg * 112 : kg * 256 + (i - 20) * 64;
        const int phase = (cta * PACE_TAU) >> 7;
        uint32_t f_due = PACE_T0 + (i <= 19
            ? phase + (i - 2) * PACE_TAU + max(i - PACE_TAIL_FROM, 0) * PACE_TAIL_EXTRA - (i > 4 ? PACE_TAU >> 3 : 0)
            : (phase >> 1) + (((18 * 8 - 2 + (i - 20) * 4) * PACE_TAU) >> 3)
              + ((((20 - PACE_TAIL_FROM) * 2 + (i - 20)) * PACE_TAIL_EXTRA) >> 1));
        f_due += __shfl_sync(0xffffffffu, t_start, 0);
        #pragma unroll 1
        for (int n = 2; n < NFILL; n++) {
            if (n == 5) bar_sync288(4);
            const uint32_t n_empty = __shfl_sync(0xffffffffu, f_empty, n), n_due = __shfl_sync(0xffffffffu, f_due, n);
            if (n_empty) mbar_wait0(n_empty);
            #pragma unroll 1
            for (uint32_t k = 0; k < SPIN_LIMIT && (int32_t)(gtime32() - n_due) < 0; k++) {}
            if (n == i && (i != 4 || cta < 112)) {
                mbar_expect_tx(f_bar, f_bytes);
                if (f_bulk) bulk_g2s(f_dst, f_ptr, SLOT, f_bar);
                else tma2d(f_dst, (const CUtensorMap*)f_ptr, f_c0, f_c1, f_bar);
                if (i == 4) tma2d(f_dst + 8192, (const CUtensorMap*)f_ptr, f_c0, 256, f_bar);
            }
        }
        return;
    }

    if (warp == 9) {
        const uint32_t cnt0 = ld_rlx(scr->cnt + hkv * 32);
        const uint4 pz = make_uint4(POISON, POISON, POISON, POISON);
        st_rlx4(scr->q + (lane >> 2) * 2048 + cta * 16 + (lane & 3) * 4, pz);
        if (lane < 16 && cta < 112) st_rlx4(scr->h + cta * 64 + lane * 4, pz);
        if (lane < 2) st_rlx4(scr->st + cta * 8 + lane * 4, pz);
        st_rlx4(scr->o + cta * 256 + lane * 4, pz);
        st_rlx4(scr->o + cta * 256 + 128 + lane * 4, pz);
        if (lane < 16) st_rlx4(reinterpret_cast<uint32_t*>(scr->acc) + cta * 64 + lane * 4, make_uint4(0u, 0u, 0u, 0u));
        __syncwarp();
        bar_arrive288(3);
        const uint32_t target = (cnt0 & ~15u) + 16u;
        if (lane == 0) {
            asm volatile("fence.acq_rel.gpu;" ::: "memory");
            asm volatile("red.relaxed.gpu.global.add.u32 [%0], 1;" :: "l"(scr->cnt + hkv * 32) : "memory");
            #pragma unroll 1
            for (uint32_t n = 0; (int32_t)(ld_acq(scr->cnt + hkv * 32) - target) < 0; n++) if (n > SPIN_LIMIT) __trap();
        }
        __syncwarp();
        bar_sync288(5);
        mbar_wait0(bar_emptyA);
        {
            const uint32_t* pq = scr->q + bb * 2048 + hkv * 256 + lane * 4;
            uint4 v0, v1;
            #pragma unroll 1
            for (uint32_t n = 0; ; n++) {
                v0 = ld_rlx4(pq); v1 = ld_rlx4(pq + 128);
                if (!__any_sync(0xffffffffu, has_poison(v0) || has_poison(v1))) break;
                if (n > SPIN_LIMIT) __trap();
            }
            const uint32_t a = sb + SM_Q + (lane >> 4) * 272 + (lane & 15) * 16;
            sts128(a, v0); sts128(a + 544, v1);
            __syncwarp();
            if (lane == 0) mbar_arrive(bar_q);
        }
        #pragma unroll 1
        for (uint32_t n = 0; __any_sync(0xffffffffu, (int32_t)(ld_acq(scr->cnt + (lane & 7) * 32) - target) < 0); n++)
            if (n > SPIN_LIMIT) __trap();
        mbar_wait0(bar_full + 12 * 8);
        {
            const uint32_t* p3 = lane < 16 ? scr->h + kg * 448 + 384 + lane * 4 : scr->st + (cta ^ 1) * 8 + (lane & 1) * 4;
            uint4 v[4];
            #pragma unroll 1
            for (uint32_t n = 0; ; n++) {
                #pragma unroll
                for (int i = 0; i < 3; i++) v[i] = ld_rlx4(scr->h + kg * 448 + i * 128 + lane * 4);
                v[3] = ld_rlx4(p3);
                if (!__any_sync(0xffffffffu, has_poison(v[0]) || has_poison(v[1]) || has_poison(v[2]) || has_poison(v[3]))) break;
                if (n > SPIN_LIMIT) __trap();
            }
            #pragma unroll
            for (int i = 0; i < 3; i++) sts128(sb + SM_H + i * 512 + lane * 16, v[i]);
            if (lane < 18) sts128(lane < 16 ? sb + SM_H + 1536 + lane * 16 : sb + SM_ST + (lane & 1) * 16, v[3]);
        }
        __syncwarp();
        if (lane == 0) mbar_arrive(bar_st);
        return;
    }

    const uint4 xa = *reinterpret_cast<const uint4*>(x + warp * 512 + lane * 8);
    const uint4 xb = *reinterpret_cast<const uint4*>(x + warp * 512 + 256 + lane * 8);
    if (lane == 0) {
        #pragma unroll 1
        for (int j = 5 + warp; j < NBAR; j += 8) mbar_init(bar_full + j * 8, j == NBAR - 1 ? 4 : 1);
        mbar_fence_init();
    }
    __syncwarp();
    bar_arrive288(4);
    bar_arrive288(5);
    {
        float xv[16];
        const uint32_t xw[8] = {xa.x, xa.y, xa.z, xa.w, xb.x, xb.y, xb.z, xb.w};
        #pragma unroll
        for (int i = 0; i < 8; i++) { xv[2 * i] = bf_lo(xw[i]); xv[2 * i + 1] = bf_hi(xw[i]); }
        float s = 0.f;
        #pragma unroll
        for (int i = 0; i < 16; i++) s += xv[i];
        #pragma unroll
        for (int o = 16; o; o >>= 1) s += __shfl_xor_sync(0xffffffffu, s, o);
        const float mean = s * (1.f / 512.f);
        float q = 0.f;
        #pragma unroll
        for (int i = 0; i < 16; i++) { const float d = xv[i] - mean; q += d * d; }
        #pragma unroll
        for (int o = 16; o; o >>= 1) q += __shfl_xor_sync(0xffffffffu, q, o);
        const float mb = bf16r(mean);
        const float den = bf16r(sqrt_approx(bf16r(bf16r(q * (1.f / 512.f)) + 1e-5f)));
        uint32_t o[8];
        #pragma unroll
        for (int i = 0; i < 8; i++)
            o[i] = pack_bf16(__fdividef(bf16r(xv[2 * i] - mb), den), __fdividef(bf16r(xv[2 * i + 1] - mb), den));
        sts128(sb + SM_XN + warp * 1040 + lane * 16, make_uint4(o[0], o[1], o[2], o[3]));
        sts128(sb + SM_XN + warp * 1040 + 512 + lane * 16, make_uint4(o[4], o[5], o[6], o[7]));
    }
    bar_sync288(2);
    bar_sync288(3);

    {
        uint32_t xf[4][2];
        #pragma unroll
        for (int s = 0; s < 4; s++) {
            const uint32_t a = sb + SM_XN + g * 1040 + (warp * 64 + s * 16 + 2 * t) * 2;
            xf[s][0] = lds32(a); xf[s][1] = lds32(a + 16);
        }
        float acc[3][4] = {};
        const int mi = lane >> 3, rr = lane & 7;
        const int krow = (warp & 3) * 64 + (mi >> 1) * 8 + rr;
        mbar_wait0(bar_full + (2 + (warp >> 2)) * 8);
        #pragma unroll
        for (int s = 0; s < 4; s++) {
            const int r = krow + s * 16;
            #pragma unroll
            for (int mt = 0; mt < 2; mt++) {
                uint32_t a[4];
                ldsm_x4_t(a, sb + (2 + (warp >> 2)) * SLOT + r * 64 + (((2 * mt + (mi & 1)) ^ ((r >> 1) & 3)) << 4));
                mma16816(acc[mt], a[0], a[1], a[2], a[3], xf[s][0], xf[s][1]);
            }
        }
        if (cta < 112) {
            mbar_wait0(bar_full + 4 * 8);
            #pragma unroll
            for (int s = 0; s < 4; s++) {
                const int r = (warp >> 2) * 256 + krow + s * 16;
                uint32_t a[4];
                ldsm_x4_t(a, sb + 4 * SLOT + r * 32 + (((mi & 1) ^ ((r >> 2) & 1)) << 4));
                mma16816(acc[2], a[0], a[1], a[2], a[3], xf[s][0], xf[s][1]);
            }
        }
        #pragma unroll
        for (int mt = 0; mt < 3; mt++)
            sts128(sb + SM_RED + (warp * 3 + mt) * 512 + lane * 16,
                   make_uint4(__float_as_uint(acc[mt][0]), __float_as_uint(acc[mt][1]), __float_as_uint(acc[mt][2]), __float_as_uint(acc[mt][3])));
    }
    bar_consumers();
    if (tid == 0) mbar_arrive(bar_emptyA);
    if (tid < 192) {
        const int tile = tid < 128 ? ((tid >> 3) & 1) : 2;
        const int b = tid < 128 ? (tid >> 4) : ((tid - 128) >> 3);
        const int j = tid & 7;
        const uint32_t a = sb + SM_RED + tile * 512 + (4 * ((2 * j) & 7) + (b >> 1)) * 16 + (2 * (j >> 2) + (b & 1)) * 4;
        float v0 = 0.f, v1 = 0.f;
        #pragma unroll
        for (int w = 0; w < 8; w++) { v0 += lds32f(a + w * 1536); v1 += lds32f(a + w * 1536 + 64); }
        if (tid < 128) {
            publish(scr->q + b * 2048 + cta * 16 + (tid & 15), pack_bf16(v0, v1));
        } else if (cta < 112) {
            v0 = bf16r(v0); v1 = bf16r(v1);
            v0 = __fdividef(v0, 1.f + __expf(-v0));
            v1 = __fdividef(v1, 1.f + __expf(-v1));
            publish(scr->h + cta * 64 + b * 8 + 2 * (j & 3) + (j >> 2), pack_bf16(v0, v1));
        }
    }

    float sc[4][4] = {};
    {
        uint4 qf[4];
        mbar_wait0(bar_q);
        #pragma unroll
        for (int j = 0; j < 4; j++) qf[j] = lds128(sb + SM_Q + (g & 3) * 272 + (4 * (j ^ (g >> 2)) + t) * 16);
        const int fill = warp < 2 ? warp : warp + 3;
        mbar_wait0(bar_full + fill * 8);
        const uint32_t kb = sb + fill * SLOT + g * 256 + t * 16;
        #pragma unroll
        for (int j = 0; j < 4; j++) {
            #pragma unroll
            for (int mt = 0; mt < 4; mt++) {
                const uint32_t a = kb + mt * 4096 + ((j ^ (g & 1)) << 6);
                const uint4 lo = lds128(a), hi = lds128(a + 2048);
                mma16816(sc[mt], lo.x, hi.x, lo.y, hi.y, qf[j].x, qf[j].y);
                mma16816(sc[mt], lo.z, hi.z, lo.w, hi.w, qf[j].z, qf[j].w);
            }
        }
        __syncwarp();
        if (lane == 0 && warp < 7) mbar_arrive(bar_emptyK + warp * 8);
    }
    const bool valid = (t >> 1) == (g & 1);
    const int h0 = 2 * (t & 1);
    {
        float m0 = -INFINITY, m1 = -INFINITY;
        #pragma unroll
        for (int mt = 0; mt < 4; mt++) {
            #pragma unroll
            for (int i = 0; i < 4; i++) sc[mt][i] = bf16r(bf16r(sc[mt][i]) * 0.08838834764831845f);
            m0 = fmaxf(m0, fmaxf(sc[mt][0], sc[mt][2]));
            m1 = fmaxf(m1, fmaxf(sc[mt][1], sc[mt][3]));
        }
        if (!valid) { m0 = -INFINITY; m1 = -INFINITY; }
        #pragma unroll
        for (int o = 2; o <= 16; o <<= 1) {
            m0 = fmaxf(m0, __shfl_xor_sync(0xffffffffu, m0, o));
            m1 = fmaxf(m1, __shfl_xor_sync(0xffffffffu, m1, o));
        }
        if (lane < 2) { sts32f(sb + SM_WMAX + warp * 16 + h0 * 4, m0); sts32f(sb + SM_WMAX + warp * 16 + h0 * 4 + 4, m1); }
    }
    bar_consumers();
    float mloc0 = -INFINITY, mloc1 = -INFINITY;
    {
        #pragma unroll
        for (int w = 0; w < 8; w++) {
            mloc0 = fmaxf(mloc0, lds32f(sb + SM_WMAX + w * 16 + h0 * 4));
            mloc1 = fmaxf(mloc1, lds32f(sb + SM_WMAX + w * 16 + h0 * 4 + 4));
        }
        const float L2E = 1.4426950408889634f;
        float l0 = 0.f, l1 = 0.f;
        const uint32_t pa = sb + SM_P + (h0 * 260 + warp * 32 + (g & 3) * 8 + (g >> 2)) * 4;
        #pragma unroll
        for (int mt = 0; mt < 4; mt++) {
            const float p0 = ex2((sc[mt][0] - mloc0) * L2E), p2 = ex2((sc[mt][2] - mloc0) * L2E);
            const float p1 = ex2((sc[mt][1] - mloc1) * L2E), p3 = ex2((sc[mt][3] - mloc1) * L2E);
            l0 += p0 + p2; l1 += p1 + p3;
            if (valid) { sts32(pa + mt * 8, pack_bf16(p0, p2)); sts32(pa + 1040 + mt * 8, pack_bf16(p1, p3)); }
        }
        if (!valid) { l0 = 0.f; l1 = 0.f; }
        #pragma unroll
        for (int o = 2; o <= 16; o <<= 1) {
            l0 += __shfl_xor_sync(0xffffffffu, l0, o);
            l1 += __shfl_xor_sync(0xffffffffu, l1, o);
        }
        if (lane < 2) { sts32f(sb + SM_WSUM + warp * 16 + h0 * 4, l0); sts32f(sb + SM_WSUM + warp * 16 + h0 * 4 + 4, l1); }
    }
    bar_consumers();
    float lloc0 = 0.f, lloc1 = 0.f;
    #pragma unroll
    for (int w = 0; w < 8; w++) {
        lloc0 += lds32f(sb + SM_WSUM + w * 16 + h0 * 4);
        lloc1 += lds32f(sb + SM_WSUM + w * 16 + h0 * 4 + 4);
    }
    if (tid < 2) {
        publish(scr->st + cta * 8 + h0, __float_as_uint(mloc0));
        publish(scr->st + cta * 8 + h0 + 1, __float_as_uint(mloc1));
        publish(scr->st + cta * 8 + 4 + h0, __float_as_uint(lloc0));
        publish(scr->st + cta * 8 + 4 + h0 + 1, __float_as_uint(lloc1));
    }

    float oa[4][4] = {};
    uint32_t* pub = scr->o + cta * 256 + h0 * 64 + warp * 8 + g;
    keep64(pub);
    float scale0 = 0.f, scale1 = 0.f;
    {
        const int mi = lane >> 3, rr = lane & 7;
        const int key = (rr >> 1) + 4 * (mi >> 1) + 8 * (rr & 1);
        const int rowp = 2 * key + (warp >> 2);
        const uint32_t voff = rowp * 128 + (((2 * (warp & 3) + (mi & 1)) ^ (rowp & 7)) << 4);
        #pragma unroll 1
        for (int vc = 0; vc < 8; vc++) {
            uint4 p0 = make_uint4(0u, 0u, 0u, 0u), p1 = p0;
            if (g < 4) {
                const uint32_t a = sb + SM_P + (g * 260 + vc * 32 + t * 8) * 4;
                p0 = lds128(a); p1 = lds128(a + 16);
            }
            if (vc == 7) {
                mbar_wait0(bar_st);
                const float L2E = 1.4426950408889634f;
                const float mo0 = lds32f(sb + SM_ST + h0 * 4), mo1 = lds32f(sb + SM_ST + h0 * 4 + 4);
                const float mg0 = fmaxf(mloc0, mo0), mg1 = fmaxf(mloc1, mo1);
                const float e0 = ex2((mloc0 - mg0) * L2E), e1 = ex2((mloc1 - mg1) * L2E);
                scale0 = __fdividef(e0, lloc0 * e0 + lds32f(sb + SM_ST + 16 + h0 * 4) * ex2((mo0 - mg0) * L2E));
                scale1 = __fdividef(e1, lloc1 * e1 + lds32f(sb + SM_ST + 20 + h0 * 4) * ex2((mo1 - mg1) * L2E));
            }
            const int fill = 11 + vc, slot = vc == 0 ? 11 : (vc < 4 ? vc + 1 : (vc < 6 ? vc - 4 : vc - 1));
            mbar_wait0(bar_full + fill * 8);
            const uint32_t vb = sb + slot * SLOT + voff;
            uint32_t a0[4], a1[4], a2[4], a3[4];
            ldsm_x4_t(a0, vb); ldsm_x4_t(a1, vb + 4096); ldsm_x4_t(a2, vb + 8192); ldsm_x4_t(a3, vb + 12288);
            mma16816(oa[0], a0[0], a0[1], a0[2], a0[3], p0.x, p0.y);
            mma16816(oa[1], a1[0], a1[1], a1[2], a1[3], p0.z, p0.w);
            mma16816(oa[2], a2[0], a2[1], a2[2], a2[3], p1.x, p1.y);
            mma16816(oa[3], a3[0], a3[1], a3[2], a3[3], p1.z, p1.w);
        }
        float os[4];
        #pragma unroll
        for (int i = 0; i < 4; i++) os[i] = (oa[0][i] + oa[1][i]) + (oa[2][i] + oa[3][i]);
        const uint32_t lo = pack_bf16(os[0] * scale0, os[1] * scale1);
        const uint32_t hi = pack_bf16(os[2] * scale0, os[3] * scale1);
        const bool odd = g & 1;
        const uint32_t y = __shfl_xor_sync(0xffffffffu, odd ? lo : hi, 4);
        const uint32_t first = odd ? y : lo, second = odd ? hi : y;
        if (t < 2) {
            publish(pub, __byte_perm(first, second, 0x5410));
            publish(pub + 64, __byte_perm(first, second, 0x7632));
        }
    }

    tail_stage(sb, kg, cg, scr, x, out);
}

typedef CUresult (*EncodeTiledFn)(CUtensorMap*, CUtensorMapDataType, cuuint32_t, void*, const cuuint64_t*, const cuuint64_t*,
                                  const cuuint32_t*, const cuuint32_t*, CUtensorMapInterleave, CUtensorMapSwizzle,
                                  CUtensorMapL2promotion, CUtensorMapFloatOOBfill);

void make_map(EncodeTiledFn enc, CUtensorMap* m, const void* base, uint64_t cols, uint64_t rows, uint32_t box_cols,
              uint32_t box_rows, CUtensorMapSwizzle sw) {
    cuuint64_t gd[2] = {cols, rows};
    cuuint64_t gs[1] = {cols * 2};
    cuuint32_t bd[2] = {box_cols, box_rows};
    cuuint32_t es[2] = {1, 1};
    enc(m, CU_TENSOR_MAP_DATA_TYPE_BFLOAT16, 2, const_cast<void*>(base), gd, gs, bd, es, CU_TENSOR_MAP_INTERLEAVE_NONE, sw,
        CU_TENSOR_MAP_L2_PROMOTION_L2_256B, CU_TENSOR_MAP_FLOAT_OOB_FILL_NONE);
}

}

extern "C" void kernel_launch(void* const* d_in, const int* in_sizes, int n_in, void* d_out, int out_size) {
    (void)in_sizes; (void)n_in; (void)out_size;
    static EncodeTiledFn enc = nullptr;
    static Scratch* scr = nullptr;
    if (!enc) {
        cudaGetSymbolAddress((void**)&scr, g_scratch);
        void* fn = nullptr;
        cudaDriverEntryPointQueryResult qr;
        cudaGetDriverEntryPoint("cuTensorMapEncodeTiled", &fn, cudaEnableDefault, &qr);
        enc = (EncodeTiledFn)fn;
        cudaFuncSetAttribute(fused_decode_kernel, cudaFuncAttributeMaxDynamicSharedMemorySize, SMEM_BYTES);
    }
    TMaps tm;
    make_map(enc, &tm.wq, d_in[3], 4096, 512, 32, 256, CU_TENSOR_MAP_SWIZZLE_64B);
    make_map(enc, &tm.w1, d_in[6], 1792, 512, 16, 256, CU_TENSOR_MAP_SWIZZLE_32B);
    make_map(enc, &tm.v, d_in[2], 64, 8ull * 8 * 4096 * 2, 64, 128, CU_TENSOR_MAP_SWIZZLE_128B);
    make_map(enc, &tm.wo, d_in[4], 512, 4096, 64, 64, CU_TENSOR_MAP_SWIZZLE_128B);
    make_map(enc, &tm.w2, d_in[7], 512, 1792, 64, 112, CU_TENSOR_MAP_SWIZZLE_128B);
    fused_decode_kernel<<<NCTA, NTHREADS, SMEM_BYTES, cudaStreamPerThread>>>(
        (const __nv_bfloat16*)d_in[1], (const __nv_bfloat16*)d_in[0], (__nv_bfloat16*)d_out, scr,
        tm);
}
```

```cpp
#include <cuda_runtime.h>
#include <cuda_bf16.h>
#include <cuda.h>
#include <stdint.h>

namespace {

constexpr int NCTA = 128;
constexpr int NTHREADS = 320;
constexpr int SLOT = 16384;
constexpr int NSLOT = 12;
constexpr int NFILL = 24;
constexpr uint32_t POISON = 0xFFFFFFFFu;
constexpr uint32_t SPIN_LIMIT = 1u << 21;

constexpr int PACE_T0 = 500, PACE_TAU = 653, PACE_TAIL_FROM = 16, PACE_TAIL_EXTRA = 70;

constexpr int SM_XN = NSLOT * SLOT;
constexpr int SM_RED = SM_XN + 8 * 1040;
constexpr int SM_P = SM_RED + 8 * 3 * 512;
constexpr int SM_WMAX = SM_P + 4 * 260 * 4;
constexpr int SM_WSUM = SM_WMAX + 128;
constexpr int SM_ST = SM_WSUM + 128;
constexpr int SM_Q = SM_ST + 32;
constexpr int SM_H = SM_Q + 4 * 272;
constexpr int SM_O = SM_RED;
constexpr int SM_BAR = SM_H + 7 * 256;
constexpr int NBAR = NFILL + 7 + 4;
constexpr int SM_TOTAL = SM_BAR + NBAR * 8;
constexpr int SMEM_BYTES = SM_TOTAL + 1024;

struct TMaps { CUtensorMap wq, w1, v, wo, w2; };

struct Scratch {
    float acc[8 * 4 * 2 * 128];
    uint32_t o[NCTA * 256];
    uint32_t q[8 * 2048];
    uint32_t h[112 * 64];
    uint32_t st[NCTA * 8];
    uint32_t cnt[8 * 32];
};
__device__ __align__(128) Scratch g_scratch;

__device__ __forceinline__ uint32_t gtime32() { uint32_t c; asm volatile("mov.u32 %0, %globaltimer_lo;" : "=r"(c)); return c; }
__device__ __forceinline__ uint32_t smem_u32(const void* p) { return (uint32_t)__cvta_generic_to_shared(p); }

__device__ __forceinline__ void mbar_init(uint32_t bar, uint32_t cnt) {
    asm volatile("mbarrier.init.shared::cta.b64 [%0], %1;" :: "r"(bar), "r"(cnt) : "memory");
}
__device__ __forceinline__ void mbar_fence_init() { asm volatile("fence.mbarrier_init.release.cluster;" ::: "memory"); }
__device__ __forceinline__ void mbar_expect_tx(uint32_t bar, uint32_t bytes) {
    asm volatile("mbarrier.arrive.expect_tx.shared::cta.b64 _, [%0], %1;" :: "r"(bar), "r"(bytes) : "memory");
}
__device__ __forceinline__ void mbar_arrive(uint32_t bar) {
    asm volatile("mbarrier.arrive.shared::cta.b64 _, [%0];" :: "r"(bar) : "memory");
}
__device__ __forceinline__ void mbar_wait0(uint32_t bar) {
    #pragma unroll 1
    for (uint32_t i = 0; i < SPIN_LIMIT; i++) {
        uint32_t ok;
        asm volatile("{\n.reg .pred p;\nmbarrier.try_wait.parity.shared::cta.b64 p, [%1], 0;\nselp.u32 %0, 1, 0, p;\n}"
                     : "=r"(ok) : "r"(bar) : "memory");
        if (ok) return;
    }
    __trap();
}
constexpr uint64_t EVICT_FIRST = 0x12F0000000000000ull;
__device__ __forceinline__ void bulk_g2s(uint32_t dst, const void* src, uint32_t bytes, uint32_t bar) {
    asm volatile("cp.async.bulk.shared::cluster.global.mbarrier::complete_tx::bytes.L2::cache_hint [%0], [%1], %2, [%3], %4;"
                 :: "r"(dst), "l"(src), "r"(bytes), "r"(bar), "l"(EVICT_FIRST) : "memory");
}
__device__ __forceinline__ void tma2d(uint32_t dst, const CUtensorMap* tm, int c0, int c1, uint32_t bar) {
    asm volatile("cp.async.bulk.tensor.2d.shared::cluster.global.mbarrier::complete_tx::bytes.L2::cache_hint [%0], [%1, {%3, %4}], [%2], %5;"
                 :: "r"(dst), "l"(tm), "r"(bar), "r"(c0), "r"(c1), "l"(EVICT_FIRST) : "memory");
}
__device__ __forceinline__ void bar_consumers() { asm volatile("bar.sync 1, 256;" ::: "memory"); }
__device__ __forceinline__ void bar_sync288(int id) { asm volatile("bar.sync %0, 288;" :: "r"(id) : "memory"); }
__device__ __forceinline__ void bar_arrive288(int id) { asm volatile("bar.arrive %0, 288;" :: "r"(id) : "memory"); }
template <typename T> __device__ __forceinline__ void keep64(T*& p) { asm volatile("" : "+l"(p)); }
__device__ __forceinline__ void keep32(uint32_t& v) { asm volatile("" : "+r"(v)); }
__device__ __forceinline__ void keepf(float& v) { asm volatile("" : "+f"(v)); }
__device__ __forceinline__ uint32_t hadd2_bf16(uint32_t a, uint32_t b) {
    uint32_t r; asm("add.rn.bf16x2 %0, %1, %2;" : "=r"(r) : "r"(a), "r"(b)); return r;
}

__device__ __forceinline__ uint4 lds128(uint32_t a) {
    uint4 v; asm volatile("ld.shared.v4.u32 {%0,%1,%2,%3}, [%4];" : "=r"(v.x), "=r"(v.y), "=r"(v.z), "=r"(v.w) : "r"(a)); return v;
}
__device__ __forceinline__ uint32_t lds32(uint32_t a) { uint32_t v; asm volatile("ld.shared.u32 %0, [%1];" : "=r"(v) : "r"(a)); return v; }
__device__ __forceinline__ float lds32f(uint32_t a) { float v; asm volatile("ld.shared.f32 %0, [%1];" : "=f"(v) : "r"(a)); return v; }
__device__ __forceinline__ void sts32(uint32_t a, uint32_t v) { asm volatile("st.shared.u32 [%0], %1;" :: "r"(a), "r"(v) : "memory"); }
__device__ __forceinline__ void sts32f(uint32_t a, float v) { asm volatile("st.shared.f32 [%0], %1;" :: "r"(a), "f"(v) : "memory"); }
__device__ __forceinline__ void sts64(uint32_t a, uint32_t x, uint32_t y) {
    asm volatile("st.shared.v2.u32 [%0], {%1,%2};" :: "r"(a), "r"(x), "r"(y) : "memory");
}
__device__ __forceinline__ void sts128(uint32_t a, uint4 v) {
    asm volatile("st.shared.v4.u32 [%0], {%1,%2,%3,%4};" :: "r"(a), "r"(v.x), "r"(v.y), "r"(v.z), "r"(v.w) : "memory");
}
__device__ __forceinline__ void ldsm_x4_t(uint32_t (&r)[4], uint32_t a) {
    asm volatile("ldmatrix.sync.aligned.m8n8.x4.trans.shared.b16 {%0,%1,%2,%3}, [%4];"
                 : "=r"(r[0]), "=r"(r[1]), "=r"(r[2]), "=r"(r[3]) : "r"(a));
}
__device__ __forceinline__ void mma16816(float (&c)[4], uint32_t a0, uint32_t a1, uint32_t a2, uint32_t a3, uint32_t b0, uint32_t b1) {
    asm volatile("mma.sync.aligned.m16n8k16.row.col.f32.bf16.bf16.f32 {%0,%1,%2,%3}, {%4,%5,%6,%7}, {%8,%9}, {%0,%1,%2,%3};"
                 : "+f"(c[0]), "+f"(c[1]), "+f"(c[2]), "+f"(c[3]) : "r"(a0), "r"(a1), "r"(a2), "r"(a3), "r"(b0), "r"(b1));
}

__device__ __forceinline__ uint32_t ld_rlx(const uint32_t* p) {
    uint32_t v; asm volatile("ld.relaxed.gpu.global.u32 %0, [%1];" : "=r"(v) : "l"(p) : "memory"); return v;
}
__device__ __forceinline__ uint32_t ld_acq(const uint32_t* p) {
    uint32_t v; asm volatile("ld.acquire.gpu.global.u32 %0, [%1];" : "=r"(v) : "l"(p) : "memory"); return v;
}
__device__ __forceinline__ uint4 ld_rlx4(const uint32_t* p) {
    uint4 v; asm volatile("ld.relaxed.gpu.global.v4.u32 {%0,%1,%2,%3}, [%4];" : "=r"(v.x), "=r"(v.y), "=r"(v.z), "=r"(v.w) : "l"(p) : "memory"); return v;
}
__device__ __forceinline__ void publish(uint32_t* p, uint32_t v) {
    asm volatile("red.relaxed.gpu.global.and.b32 [%0], %1;" :: "l"(p), "r"(v == POISON ? 0x7FFFFFFFu : v) : "memory");
}
__device__ __forceinline__ void st_rlx4(uint32_t* p, uint4 v) {
    asm volatile("st.relaxed.gpu.global.v4.u32 [%0], {%1,%2,%3,%4};" :: "l"(p), "r"(v.x), "r"(v.y), "r"(v.z), "r"(v.w) : "memory");
}
__device__ __forceinline__ bool has_poison(const uint4& v) {
    return v.x == POISON || v.y == POISON || v.z == POISON || v.w == POISON;
}

__device__ __forceinline__ float sqrt_approx(float x) { float r; asm("sqrt.approx.f32 %0, %1;" : "=f"(r) : "f"(x)); return r; }
__device__ __forceinline__ float ex2(float x) { float r; asm("ex2.approx.ftz.f32 %0, %1;" : "=f"(r) : "f"(x)); return r; }
__device__ __forceinline__ float bf16r(float x) { return __bfloat162float(__float2bfloat16_rn(x)); }
__device__ __forceinline__ uint32_t pack_bf16(float lo, float hi) {
    uint32_t r; asm("cvt.rn.bf16x2.f32 %0, %1, %2;" : "=r"(r) : "f"(hi), "f"(lo)); return r;
}
__device__ __forceinline__ float bf_lo(uint32_t w) { return __uint_as_float(w << 16); }
__device__ __forceinline__ float bf_hi(uint32_t w) { return __uint_as_float(w & 0xFFFF0000u); }

__device__ __forceinline__ void tail_stage(const uint32_t sb, const int kg, const int cg, Scratch* __restrict__ scr,
                                        const __nv_bfloat16* __restrict__ x, __nv_bfloat16* __restrict__ out)
{
    const int tid = threadIdx.x, warp = tid >> 5, lane = tid & 31, g = lane >> 2, t = lane & 3;
    const uint32_t bar_full = sb + SM_BAR, bar_o = bar_full + (NBAR - 1) * 8;
    if (warp >= 4) {
        const uint32_t* po = scr->o + ((kg >> 1) * 16 + (warp - 4) * 4) * 256 + (kg & 1) * 128 + lane * 4;
        uint32_t so = sb + SM_O + (warp - 4) * 1152 + (lane >> 2) * 64 + (lane & 1) * 32 + (lane & 2) * 4;
        keep64(po); keep32(so);
        mbar_wait0(bar_full + 19 * 8);
        uint4 v[4];
        #pragma unroll
        for (int i = 0; i < 4; i++) v[i] = ld_rlx4(po + i * 256);
        #pragma unroll 1
        for (uint32_t n = 0; ; n++) {
            bool bad[4];
            #pragma unroll
            for (int i = 0; i < 4; i++) bad[i] = __any_sync(0xffffffffu, has_poison(v[i]));
            if (!(bad[0] || bad[1] || bad[2] || bad[3])) break;
            #pragma unroll
            for (int i = 0; i < 4; i++) if (bad[i]) v[i] = ld_rlx4(po + i * 256);
            if (n > SPIN_LIMIT) __trap();
        }
        #pragma unroll
        for (int i = 0; i < 2; i++) {
            sts64(so + i * 576, hadd2_bf16(v[2 * i].x, v[2 * i + 1].x), hadd2_bf16(v[2 * i].y, v[2 * i + 1].y));
            sts64(so + i * 576 + 16, hadd2_bf16(v[2 * i].z, v[2 * i + 1].z), hadd2_bf16(v[2 * i].w, v[2 * i + 1].w));
        }
        __syncwarp();
        if (lane == 0) mbar_arrive(bar_o);
        return;
    }
    float acc[8][4] = {};
    uint32_t wa[4][4][4];
    const int mi = lane >> 3, rr = lane & 7;
    uint32_t wb = sb + 8 * SLOT + ((mi >> 1) * 8 + rr) * 128 + (((2 * warp + (mi & 1)) ^ rr) << 4);
    uint32_t so = sb + SM_O + g * 576 + t * 16;
    const int ocol = 64 * cg + 16 * warp + g;
    float* pacc = scr->acc + (cg * 4 + warp) * 256 + lane * 4;
    __nv_bfloat16* pout = out + 2 * t * 512 + ocol;
    keep32(wb); keep32(so); keep64(pacc); keep64(pout);
    const __nv_bfloat16* px = x + 2 * t * 512 + ocol;
    const __nv_bfloat16 b0 = px[0], b1 = px[512], b2 = px[8], b3 = px[520];
    mbar_wait0(bar_full + 19 * 8);
    #pragma unroll
    for (int i = 0; i < 7; i++) {
        uint32_t a[4];
        ldsm_x4_t(a, wb - SLOT + i * 2048);
        const uint32_t ha = sb + SM_H + i * 256 + lane * 8;
        mma16816(acc[i], a[0], a[1], a[2], a[3], lds32(ha), lds32(ha + 4));
    }
    float x0 = __bfloat162float(b0), x1 = __bfloat162float(b1), x2 = __bfloat162float(b2), x3 = __bfloat162float(b3);
    keepf(x0); keepf(x1); keepf(x2); keepf(x3);
    uint4 of[8];
    #pragma unroll
    for (int pc = 0; pc < 3; pc++) {
        mbar_wait0(bar_full + (20 + pc) * 8);
        #pragma unroll
        for (int k = 0; k < 4; k++) ldsm_x4_t(wa[pc][k], wb + pc * 8192 + k * 2048);
    }
    mbar_wait0(bar_o);
    #pragma unroll
    for (int i = 0; i < 8; i++) of[i] = lds128(so + i * 64);
    #pragma unroll
    for (int pc = 0; pc < 4; pc++) {
        if (pc == 3) {
            #pragma unroll
            for (int i = 0; i < 4; i++) acc[0][i] = (acc[0][i] + acc[1][i]) + (acc[2][i] + acc[3][i]);
            mbar_wait0(bar_full + (20 + pc) * 8);
            #pragma unroll
            for (int k = 0; k < 4; k++) ldsm_x4_t(wa[pc][k], wb + pc * 8192 + k * 2048);
        }
        #pragma unroll
        for (int k = 0; k < 4; k++) {
            const uint4& u = of[2 * pc + (k >> 1)];
            mma16816(acc[(pc & 1) * 4 + k], wa[pc][k][0], wa[pc][k][1], wa[pc][k][2], wa[pc][k][3], k & 1 ? u.z : u.x, k & 1 ? u.w : u.y);
        }
    }
    float r[4];
    #pragma unroll
    for (int i = 0; i < 4; i++) r[i] = (acc[4][i] + acc[5][i]) + (acc[6][i] + acc[7][i]) + acc[0][i];
    float4 o0, o1;
    asm volatile("atom.relaxed.gpu.global.add.v4.f32 {%0,%1,%2,%3}, [%4], {%5,%6,%7,%8};"
                 : "=f"(o0.x), "=f"(o0.y), "=f"(o0.z), "=f"(o0.w) : "l"(pacc), "f"(r[0]), "f"(r[1]), "f"(1.f), "f"(0.f) : "memory");
    asm volatile("atom.relaxed.gpu.global.add.v4.f32 {%0,%1,%2,%3}, [%4], {%5,%6,%7,%8};"
                 : "=f"(o1.x), "=f"(o1.y), "=f"(o1.z), "=f"(o1.w) : "l"(pacc + 128), "f"(r[2]), "f"(r[3]), "f"(1.f), "f"(0.f) : "memory");
    r[0] += x0; r[1] += x1; r[2] += x2; r[3] += x3;
    if (o0.z == 15.f) {
        pout[0] = __float2bfloat16_rn(o0.x + r[0]);
        pout[512] = __float2bfloat16_rn(o0.y + r[1]);
    }
    if (o1.z == 15.f) {
        pout[8] = __float2bfloat16_rn(o1.x + r[2]);
        pout[520] = __float2bfloat16_rn(o1.y + r[3]);
    }
}

template <bool SCALED>
__global__ void __launch_bounds__(NTHREADS, 1)
fused_decode_kernel(const __nv_bfloat16* __restrict__ kcache, const __nv_bfloat16* __restrict__ x,
                    __nv_bfloat16* __restrict__ out, Scratch* __restrict__ scr, const uint32_t pace_scale_q10,
                    const __grid_constant__ TMaps tm)
{
    extern __shared__ uint8_t smem_raw[];
    const uint32_t sb = (smem_u32(smem_raw) + 1023u) & ~1023u;
    const int tid = threadIdx.x, warp = tid >> 5, lane = tid & 31;
    const int cta = blockIdx.x;
    const int hkv = cta >> 4, bb = (cta >> 1) & 7, half = cta & 1;
    const int kg = cta >> 3, cg = cta & 7;
    const int g = lane >> 2, t = lane & 3;
    const uint32_t bar_full = sb + SM_BAR, bar_emptyK = bar_full + NFILL * 8, bar_emptyA = bar_emptyK + 7 * 8;
    const uint32_t bar_q = bar_emptyA + 8, bar_st = bar_q + 8;

    const int kvrow0 = (bb * 8 + hkv) * 4096 + 3072 + half * 512;
    uint32_t t_start = 0;
    if (tid == 0)
        asm volatile("cp.async.bulk.prefetch.L2.global.L2::cache_hint [%0], %1, %2;"
                     :: "l"(kcache + (size_t)kvrow0 * 128), "r"(2 * SLOT), "l"(EVICT_FIRST) : "memory");
    if (tid == 256) {
        mbar_init(bar_full, 1);
        mbar_init(bar_full + 8, 1);
        mbar_fence_init();
        mbar_expect_tx(bar_full, SLOT);
        bulk_g2s(sb, kcache + (size_t)kvrow0 * 128, SLOT, bar_full);
        mbar_expect_tx(bar_full + 8, SLOT);
        bulk_g2s(sb + SLOT, kcache + (size_t)(kvrow0 + 64) * 128, SLOT, bar_full + 8);
        t_start = gtime32();
    }

    if (warp == 8) {
        if (lane == 0) {
            asm volatile("prefetch.tensormap [%0];" :: "l"(&tm.wq));
            asm volatile("prefetch.tensormap [%0];" :: "l"(&tm.w1));
            asm volatile("prefetch.tensormap [%0];" :: "l"(&tm.v));
            asm volatile("prefetch.tensormap [%0];" :: "l"(&tm.wo));
            asm volatile("prefetch.tensormap [%0];" :: "l"(&tm.w2));
            mbar_init(bar_full + 16, 1); mbar_init(bar_full + 24, 1); mbar_init(bar_full + 32, 1);
            mbar_fence_init();
        }
        __syncwarp();
        bar_arrive288(2);
        const int i = lane;
        const int slot = i < NSLOT ? i : (i < 15 ? i - 10 : (i < 17 ? i - 15 : (i < 20 ? i - NSLOT : 8 + ((i - 20) >> 1))));
        const uint32_t f_empty = i < NSLOT ? 0u : (i < 15 ? bar_emptyA : bar_emptyK + (slot < 2 ? slot : slot - 3) * 8);
        const uint32_t f_bar = bar_full + i * 8;
        const uint32_t f_dst = sb + slot * SLOT + (i >= 20 ? (i & 1) * 8192 : 0);
        const uint32_t f_bytes = i >= 20 ? SLOT / 2 : (i == 19 ? 112 * 128 : SLOT);
        const bool f_bulk = i >= 5 && i <= 10;
        const void* f_ptr = i <= 3 ? (const void*)&tm.wq : i == 4 ? (const void*)&tm.w1
                          : f_bulk ? (const void*)(kcache + (size_t)(kvrow0 + ((i - 3) & 7) * 64) * 128)
                          : i <= 18 ? (const void*)&tm.v : i == 19 ? (const void*)&tm.w2 : (const void*)&tm.wo;
        const int f_c0 = i <= 3 ? cta * 32 : i == 4 ? cta * 16 : i <= 18 ? 0 : cg * 64;
        const int f_c1 = i <= 3 ? (i - 2) * 256 : i == 4 ? 0 : i <= 18 ? (kvrow0 + ((i - 11) & 7) * 64) * 2
                       : i == 19 ? kg * 112 : kg * 256 + (i - 20) * 64;
        const int phase = (cta * PACE_TAU) >> 7;
        uint32_t f_due = PACE_T0 + (i <= 19
            ? phase + (i - 2) * PACE_TAU + max(i - PACE_TAIL_FROM, 0) * PACE_TAIL_EXTRA - (i > 4 ? PACE_TAU >> 3 : 0)
            : (phase >> 1) + (((18 * 8 - 2 + (i - 20) * 4) * PACE_TAU) >> 3)
              + ((((20 - PACE_TAIL_FROM) * 2 + (i - 20)) * PACE_TAIL_EXTRA) >> 1));
        if (SCALED) f_due = (f_due * pace_scale_q10) >> 10;
        f_due += __shfl_sync(0xffffffffu, t_start, 0);
        #pragma unroll 1
        for (int n = 2; n < NFILL; n++) {
            if (n == 5) bar_sync288(4);
            const uint32_t n_empty = __shfl_sync(0xffffffffu, f_empty, n), n_due = __shfl_sync(0xffffffffu, f_due, n);
            if (n_empty) mbar_wait0(n_empty);
            #pragma unroll 1
            for (uint32_t k = 0; k < SPIN_LIMIT && (int32_t)(gtime32() - n_due) < 0; k++) {}
            if (n == i && (i != 4 || cta < 112)) {
                mbar_expect_tx(f_bar, f_bytes);
                if (f_bulk) bulk_g2s(f_dst, f_ptr, SLOT, f_bar);
                else tma2d(f_dst, (const CUtensorMap*)f_ptr, f_c0, f_c1, f_bar);
                if (i == 4) tma2d(f_dst + 8192, (const CUtensorMap*)f_ptr, f_c0, 256, f_bar);
            }
        }
        return;
    }

    if (warp == 9) {
        const uint32_t cnt0 = ld_rlx(scr->cnt + hkv * 32);
        const uint4 pz = make_uint4(POISON, POISON, POISON, POISON);
        st_rlx4(scr->q + (lane >> 2) * 2048 + cta * 16 + (lane & 3) * 4, pz);
        if (lane < 16 && cta < 112) st_rlx4(scr->h + cta * 64 + lane * 4, pz);
        if (lane < 2) st_rlx4(scr->st + cta * 8 + lane * 4, pz);
        st_rlx4(scr->o + cta * 256 + lane * 4, pz);
        st_rlx4(scr->o + cta * 256 + 128 + lane * 4, pz);
        if (lane < 16) st_rlx4(reinterpret_cast<uint32_t*>(scr->acc) + cta * 64 + lane * 4, make_uint4(0u, 0u, 0u, 0u));
        __syncwarp();
        bar_arrive288(3);
        const uint32_t target = (__shfl_sync(0xffffffffu, cnt0, 0) & ~15u) + 16u;
        if (lane == 0) {
            asm volatile("fence.acq_rel.gpu;" ::: "memory");
            asm volatile("red.relaxed.gpu.global.add.u32 [%0], 1;" :: "l"(scr->cnt + hkv * 32) : "memory");
            #pragma unroll 1
            for (uint32_t n = 0; (int32_t)(ld_acq(scr->cnt + hkv * 32) - target) < 0; n++) if (n > SPIN_LIMIT) __trap();
        }
        __syncwarp();
        bar_sync288(5);
        mbar_wait0(bar_emptyA);
        {
            const uint32_t* pq = scr->q + bb * 2048 + hkv * 256 + lane * 4;
            uint4 v0, v1;
            #pragma unroll 1
            for (uint32_t n = 0; ; n++) {
                v0 = ld_rlx4(pq); v1 = ld_rlx4(pq + 128);
                if (!__any_sync(0xffffffffu, has_poison(v0) || has_poison(v1))) break;
                if (n > SPIN_LIMIT) __trap();
            }
            const uint32_t a = sb + SM_Q + (lane >> 4) * 272 + (lane & 15) * 16;
            sts128(a, v0); sts128(a + 544, v1);
            __syncwarp();
            if (lane == 0) mbar_arrive(bar_q);
        }
        #pragma unroll 1
        for (uint32_t n = 0; __any_sync(0xffffffffu, (int32_t)(ld_acq(scr->cnt + (lane & 7) * 32) - target) < 0); n++)
            if (n > SPIN_LIMIT) __trap();
        mbar_wait0(bar_full + 12 * 8);
        {
            const uint32_t* p3 = lane < 16 ? scr->h + kg * 448 + 384 + lane * 4 : scr->st + (cta ^ 1) * 8 + (lane & 1) * 4;
            uint4 v[4];
            #pragma unroll 1
            for (uint32_t n = 0; ; n++) {
                #pragma unroll
                for (int i = 0; i < 3; i++) v[i] = ld_rlx4(scr->h + kg * 448 + i * 128 + lane * 4);
                v[3] = ld_rlx4(p3);
                if (!__any_sync(0xffffffffu, has_poison(v[0]) || has_poison(v[1]) || has_poison(v[2]) || has_poison(v[3]))) break;
                if (n > SPIN_LIMIT) __trap();
            }
            #pragma unroll
            for (int i = 0; i < 3; i++) sts128(sb + SM_H + i * 512 + lane * 16, v[i]);
            if (lane < 18) sts128(lane < 16 ? sb + SM_H + 1536 + lane * 16 : sb + SM_ST + (lane & 1) * 16, v[3]);
        }
        __syncwarp();
        if (lane == 0) mbar_arrive(bar_st);
        return;
    }

    const uint4 xa = *reinterpret_cast<const uint4*>(x + warp * 512 + lane * 8);
    const uint4 xb = *reinterpret_cast<const uint4*>(x + warp * 512 + 256 + lane * 8);
    if (lane == 0) {
        #pragma unroll 1
        for (int j = 5 + warp; j < NBAR; j += 8) mbar_init(bar_full + j * 8, j == NBAR - 1 ? 4 : 1);
        mbar_fence_init();
    }
    __syncwarp();
    bar_arrive288(4);
    bar_arrive288(5);
    {
        float xv[16];
        const uint32_t xw[8] = {xa.x, xa.y, xa.z, xa.w, xb.x, xb.y, xb.z, xb.w};
        #pragma unroll
        for (int i = 0; i < 8; i++) { xv[2 * i] = bf_lo(xw[i]); xv[2 * i + 1] = bf_hi(xw[i]); }
        float s = 0.f;
        #pragma unroll
        for (int i = 0; i < 16; i++) s += xv[i];
        #pragma unroll
        for (int o = 16; o; o >>= 1) s += __shfl_xor_sync(0xffffffffu, s, o);
        const float mean = s * (1.f / 512.f);
        float q = 0.f;
        #pragma unroll
        for (int i = 0; i < 16; i++) { const float d = xv[i] - mean; q += d * d; }
        #pragma unroll
        for (int o = 16; o; o >>= 1) q += __shfl_xor_sync(0xffffffffu, q, o);
        const float mb = bf16r(mean);
        const float den = bf16r(sqrt_approx(bf16r(bf16r(q * (1.f / 512.f)) + 1e-5f)));
        uint32_t o[8];
        #pragma unroll
        for (int i = 0; i < 8; i++)
            o[i] = pack_bf16(__fdividef(bf16r(xv[2 * i] - mb), den), __fdividef(bf16r(xv[2 * i + 1] - mb), den));
        sts128(sb + SM_XN + warp * 1040 + lane * 16, make_uint4(o[0], o[1], o[2], o[3]));
        sts128(sb + SM_XN + warp * 1040 + 512 + lane * 16, make_uint4(o[4], o[5], o[6], o[7]));
    }
    bar_sync288(2);
    bar_sync288(3);

    {
        uint32_t xf[4][2];
        #pragma unroll
        for (int s = 0; s < 4; s++) {
            const uint32_t a = sb + SM_XN + g * 1040 + (warp * 64 + s * 16 + 2 * t) * 2;
            xf[s][0] = lds32(a); xf[s][1] = lds32(a + 16);
        }
        float acc[3][4] = {};
        const int mi = lane >> 3, rr = lane & 7;
        const int krow = (warp & 3) * 64 + (mi >> 1) * 8 + rr;
        mbar_wait0(bar_full + (2 + (warp >> 2)) * 8);
        #pragma unroll
        for (int s = 0; s < 4; s++) {
            const int r = krow + s * 16;
            #pragma unroll
            for (int mt = 0; mt < 2; mt++) {
                uint32_t a[4];
                ldsm_x4_t(a, sb + (2 + (warp >> 2)) * SLOT + r * 64 + (((2 * mt + (mi & 1)) ^ ((r >> 1) & 3)) << 4));
                mma16816(acc[mt], a[0], a[1], a[2], a[3], xf[s][0], xf[s][1]);
            }
        }
        if (cta < 112) {
            mbar_wait0(bar_full + 4 * 8);
            #pragma unroll
            for (int s = 0; s < 4; s++) {
                const int r = (warp >> 2) * 256 + krow + s * 16;
                uint32_t a[4];
                ldsm_x4_t(a, sb + 4 * SLOT + r * 32 + (((mi & 1) ^ ((r >> 2) & 1)) << 4));
                mma16816(acc[2], a[0], a[1], a[2], a[3], xf[s][0], xf[s][1]);
            }
        }
        #pragma unroll
        for (int mt = 0; mt < 3; mt++)
            sts128(sb + SM_RED + (warp * 3 + mt) * 512 + lane * 16,
                   make_uint4(__float_as_uint(acc[mt][0]), __float_as_uint(acc[mt][1]), __float_as_uint(acc[mt][2]), __float_as_uint(acc[mt][3])));
    }
    bar_consumers();
    if (tid == 0) mbar_arrive(bar_emptyA);
    if (tid < 192) {
        const int tile = tid < 128 ? ((tid >> 3) & 1) : 2;
        const int b = tid < 128 ? (tid >> 4) : ((tid - 128) >> 3);
        const int j = tid & 7;
        const uint32_t a = sb + SM_RED + tile * 512 + (4 * ((2 * j) & 7) + (b >> 1)) * 16 + (2 * (j >> 2) + (b & 1)) * 4;
        float v0 = 0.f, v1 = 0.f;
        #pragma unroll
        for (int w = 0; w < 8; w++) { v0 += lds32f(a + w * 1536); v1 += lds32f(a + w * 1536 + 64); }
        if (tid < 128) {
            publish(scr->q + b * 2048 + cta * 16 + (tid & 15), pack_bf16(v0, v1));
        } else if (cta < 112) {
            v0 = bf16r(v0); v1 = bf16r(v1);
            v0 = __fdividef(v0, 1.f + __expf(-v0));
            v1 = __fdividef(v1, 1.f + __expf(-v1));
            publish(scr->h + cta * 64 + b * 8 + 2 * (j & 3) + (j >> 2), pack_bf16(v0, v1));
        }
    }

    float sc[4][4] = {};
    {
        uint4 qf[4];
        mbar_wait0(bar_q);
        #pragma unroll
        for (int j = 0; j < 4; j++) qf[j] = lds128(sb + SM_Q + (g & 3) * 272 + (4 * (j ^ (g >> 2)) + t) * 16);
        const int fill = warp < 2 ? warp : warp + 3;
        mbar_wait0(bar_full + fill * 8);
        const uint32_t kb = sb + fill * SLOT + g * 256 + t * 16;
        #pragma unroll
        for (int j = 0; j < 4; j++) {
            #pragma unroll
            for (int mt = 0; mt < 4; mt++) {
                const uint32_t a = kb + mt * 4096 + ((j ^ (g & 1)) << 6);
                const uint4 lo = lds128(a), hi = lds128(a + 2048);
                mma16816(sc[mt], lo.x, hi.x, lo.y, hi.y, qf[j].x, qf[j].y);
                mma16816(sc[mt], lo.z, hi.z, lo.w, hi.w, qf[j].z, qf[j].w);
            }
        }
        __syncwarp();
        if (lane == 0 && warp < 7) mbar_arrive(bar_emptyK + warp * 8);
    }
    const bool valid = (t >> 1) == (g & 1);
    const int h0 = 2 * (t & 1);
    {
        float m0 = -INFINITY, m1 = -INFINITY;
        #pragma unroll
        for (int mt = 0; mt < 4; mt++) {
            #pragma unroll
            for (int i = 0; i < 4; i++) sc[mt][i] = bf16r(bf16r(sc[mt][i]) * 0.08838834764831845f);
            m0 = fmaxf(m0, fmaxf(sc[mt][0], sc[mt][2]));
            m1 = fmaxf(m1, fmaxf(sc[mt][1], sc[mt][3]));
        }
        if (!valid) { m0 = -INFINITY; m1 = -INFINITY; }
        #pragma unroll
        for (int o = 2; o <= 16; o <<= 1) {
            m0 = fmaxf(m0, __shfl_xor_sync(0xffffffffu, m0, o));
            m1 = fmaxf(m1, __shfl_xor_sync(0xffffffffu, m1, o));
        }
        if (lane < 2) { sts32f(sb + SM_WMAX + warp * 16 + h0 * 4, m0); sts32f(sb + SM_WMAX + warp * 16 + h0 * 4 + 4, m1); }
    }
    bar_consumers();
    float mloc0 = -INFINITY, mloc1 = -INFINITY;
    {
        #pragma unroll
        for (int w = 0; w < 8; w++) {
            mloc0 = fmaxf(mloc0, lds32f(sb + SM_WMAX + w * 16 + h0 * 4));
            mloc1 = fmaxf(mloc1, lds32f(sb + SM_WMAX + w * 16 + h0 * 4 + 4));
        }
        const float L2E = 1.4426950408889634f;
        float l0 = 0.f, l1 = 0.f;
        const uint32_t pa = sb + SM_P + (h0 * 260 + warp * 32 + (g & 3) * 8 + (g >> 2)) * 4;
        #pragma unroll
        for (int mt = 0; mt < 4; mt++) {
            const float p0 = ex2((sc[mt][0] - mloc0) * L2E), p2 = ex2((sc[mt][2] - mloc0) * L2E);
            const float p1 = ex2((sc[mt][1] - mloc1) * L2E), p3 = ex2((sc[mt][3] - mloc1) * L2E);
            l0 += p0 + p2; l1 += p1 + p3;
            if (valid) { sts32(pa + mt * 8, pack_bf16(p0, p2)); sts32(pa + 1040 + mt * 8, pack_bf16(p1, p3)); }
        }
        if (!valid) { l0 = 0.f; l1 = 0.f; }
        #pragma unroll
        for (int o = 2; o <= 16; o <<= 1) {
            l0 += __shfl_xor_sync(0xffffffffu, l0, o);
            l1 += __shfl_xor_sync(0xffffffffu, l1, o);
        }
        if (lane < 2) { sts32f(sb + SM_WSUM + warp * 16 + h0 * 4, l0); sts32f(sb + SM_WSUM + warp * 16 + h0 * 4 + 4, l1); }
    }
    bar_consumers();
    float lloc0 = 0.f, lloc1 = 0.f;
    #pragma unroll
    for (int w = 0; w < 8; w++) {
        lloc0 += lds32f(sb + SM_WSUM + w * 16 + h0 * 4);
        lloc1 += lds32f(sb + SM_WSUM + w * 16 + h0 * 4 + 4);
    }
    if (tid < 2) {
        publish(scr->st + cta * 8 + h0, __float_as_uint(mloc0));
        publish(scr->st + cta * 8 + h0 + 1, __float_as_uint(mloc1));
        publish(scr->st + cta * 8 + 4 + h0, __float_as_uint(lloc0));
        publish(scr->st + cta * 8 + 4 + h0 + 1, __float_as_uint(lloc1));
    }

    float oa[4][4] = {};
    uint32_t* pub = scr->o + cta * 256 + h0 * 64 + warp * 8 + g;
    keep64(pub);
    float scale0 = 0.f, scale1 = 0.f;
    {
        const int mi = lane >> 3, rr = lane & 7;
        const int key = (rr >> 1) + 4 * (mi >> 1) + 8 * (rr & 1);
        const int rowp = 2 * key + (warp >> 2);
        const uint32_t voff = rowp * 128 + (((2 * (warp & 3) + (mi & 1)) ^ (rowp & 7)) << 4);
        #pragma unroll 1
        for (int vc = 0; vc < 8; vc++) {
            uint4 p0 = make_uint4(0u, 0u, 0u, 0u), p1 = p0;
            if (g < 4) {
                const uint32_t a = sb + SM_P + (g * 260 + vc * 32 + t * 8) * 4;
                p0 = lds128(a); p1 = lds128(a + 16);
            }
            if (vc == 7) {
                mbar_wait0(bar_st);
                const float L2E = 1.4426950408889634f;
                const float mo0 = lds32f(sb + SM_ST + h0 * 4), mo1 = lds32f(sb + SM_ST + h0 * 4 + 4);
                const float mg0 = fmaxf(mloc0, mo0), mg1 = fmaxf(mloc1, mo1);
                const float e0 = ex2((mloc0 - mg0) * L2E), e1 = ex2((mloc1 - mg1) * L2E);
                scale0 = __fdividef(e0, lloc0 * e0 + lds32f(sb + SM_ST + 16 + h0 * 4) * ex2((mo0 - mg0) * L2E));
                scale1 = __fdividef(e1, lloc1 * e1 + lds32f(sb + SM_ST + 20 + h0 * 4) * ex2((mo1 - mg1) * L2E));
            }
            const int fill = 11 + vc, slot = vc == 0 ? 11 : (vc < 4 ? vc + 1 : (vc < 6 ? vc - 4 : vc - 1));
            mbar_wait0(bar_full + fill * 8);
            const uint32_t vb = sb + slot * SLOT + voff;
            uint32_t a0[4], a1[4], a2[4], a3[4];
            ldsm_x4_t(a0, vb); ldsm_x4_t(a1, vb + 4096); ldsm_x4_t(a2, vb + 8192); ldsm_x4_t(a3, vb + 12288);
            mma16816(oa[0], a0[0], a0[1], a0[2], a0[3], p0.x, p0.y);
            mma16816(oa[1], a1[0], a1[1], a1[2], a1[3], p0.z, p0.w);
            mma16816(oa[2], a2[0], a2[1], a2[2], a2[3], p1.x, p1.y);
            mma16816(oa[3], a3[0], a3[1], a3[2], a3[3], p1.z, p1.w);
        }
        float os[4];
        #pragma unroll
        for (int i = 0; i < 4; i++) os[i] = (oa[0][i] + oa[1][i]) + (oa[2][i] + oa[3][i]);
        const uint32_t lo = pack_bf16(os[0] * scale0, os[1] * scale1);
        const uint32_t hi = pack_bf16(os[2] * scale0, os[3] * scale1);
        const bool odd = g & 1;
        const uint32_t y = __shfl_xor_sync(0xffffffffu, odd ? lo : hi, 4);
        const uint32_t first = odd ? y : lo, second = odd ? hi : y;
        if (t < 2) {
            publish(pub, __byte_perm(first, second, 0x5410));
            publish(pub + 64, __byte_perm(first, second, 0x7632));
        }
    }

    tail_stage(sb, kg, cg, scr, x, out);
}

typedef CUresult (*EncodeTiledFn)(CUtensorMap*, CUtensorMapDataType, cuuint32_t, void*, const cuuint64_t*, const cuuint64_t*,
                                  const cuuint32_t*, const cuuint32_t*, CUtensorMapInterleave, CUtensorMapSwizzle,
                                  CUtensorMapL2promotion, CUtensorMapFloatOOBfill);

void make_map(EncodeTiledFn enc, CUtensorMap* m, const void* base, uint64_t cols, uint64_t rows, uint32_t box_cols,
              uint32_t box_rows, CUtensorMapSwizzle sw) {
    cuuint64_t gd[2] = {cols, rows};
    cuuint64_t gs[1] = {cols * 2};
    cuuint32_t bd[2] = {box_cols, box_rows};
    cuuint32_t es[2] = {1, 1};
    enc(m, CU_TENSOR_MAP_DATA_TYPE_BFLOAT16, 2, const_cast<void*>(base), gd, gs, bd, es, CU_TENSOR_MAP_INTERLEAVE_NONE, sw,
        CU_TENSOR_MAP_L2_PROMOTION_L2_256B, CU_TENSOR_MAP_FLOAT_OOB_FILL_NONE);
}

}

extern "C" void kernel_launch(void* const* d_in, const int* in_sizes, int n_in, void* d_out, int out_size) {
    (void)in_sizes; (void)n_in; (void)out_size;
    static EncodeTiledFn enc = nullptr;
    static Scratch* scr = nullptr;
    static uint32_t scale_q10 = 1024;
    if (!enc) {
        int dev = 0, khz = 0, bits = 0;
        cudaGetDevice(&dev);
        cudaDeviceGetAttribute(&khz, cudaDevAttrMemoryClockRate, dev);
        cudaDeviceGetAttribute(&bits, cudaDevAttrGlobalMemoryBusWidth, dev);
        if (khz > 0 && bits > 0) scale_q10 = (uint32_t)(1024.0 * (2619000.0 * 5120.0) / ((double)khz * bits) + 0.5);
        cudaGetSymbolAddress((void**)&scr, g_scratch);
        void* fn = nullptr;
        cudaDriverEntryPointQueryResult qr;
        cudaGetDriverEntryPoint("cuTensorMapEncodeTiled", &fn, cudaEnableDefault, &qr);
        enc = (EncodeTiledFn)fn;
        cudaFuncSetAttribute(fused_decode_kernel<false>, cudaFuncAttributeMaxDynamicSharedMemorySize, SMEM_BYTES);
        cudaFuncSetAttribute(fused_decode_kernel<true>, cudaFuncAttributeMaxDynamicSharedMemorySize, SMEM_BYTES);
    }
    TMaps tm;
    make_map(enc, &tm.wq, d_in[3], 4096, 512, 32, 256, CU_TENSOR_MAP_SWIZZLE_64B);
    make_map(enc, &tm.w1, d_in[6], 1792, 512, 16, 256, CU_TENSOR_MAP_SWIZZLE_32B);
    make_map(enc, &tm.v, d_in[2], 64, 8ull * 8 * 4096 * 2, 64, 128, CU_TENSOR_MAP_SWIZZLE_128B);
    make_map(enc, &tm.wo, d_in[4], 512, 4096, 64, 64, CU_TENSOR_MAP_SWIZZLE_128B);
    make_map(enc, &tm.w2, d_in[7], 512, 1792, 64, 112, CU_TENSOR_MAP_SWIZZLE_128B);
    auto* kern = scale_q10 == 1024 ? fused_decode_kernel<false> : fused_decode_kernel<true>;
    kern<<<NCTA, NTHREADS, SMEM_BYTES, cudaStreamPerThread>>>(
        (const __nv_bfloat16*)d_in[1], (const __nv_bfloat16*)d_in[0], (__nv_bfloat16*)d_out, scr, scale_q10, tm);
}
```
